```python
import torch

def _softmax(x, axis=-1):
    return torch.softmax(x, dim=axis)

def _gelu(x):
    return torch.nn.functional.gelu(x, approximate='tanh')

def _silu(x):
    return torch.nn.functional.silu(x)

def _sigmoid(x):
    return torch.sigmoid(x)

def _layernorm(x, axis=-1, eps=1e-05):
    m = x.mean(dim=axis, keepdim=True)
    v = x.var(dim=axis, keepdim=True, unbiased=False)
    return (x - m) / torch.sqrt(v + eps)

def _scatter_add(tgt, idx, src, axis=0):
    return tgt.clone().index_add_(axis, idx, src)

def _segment_sum(src, seg, n):
    out = torch.zeros((n,) + src.shape[1:], dtype=src.dtype)
    return out.index_add_(0, seg, src)

def _pad(x, pw):
    flat = tuple((v for pair in reversed(pw) for v in pair))
    return torch.nn.functional.pad(x, flat)
kernel_name = 'parallel_sum__ssm_conv_h3__mixer_gmlp__prompt'

def setup_inputs():

    _w = lambda a: (lambda t: t.to(torch.bfloat16) if t.is_floating_point() else t)(torch.as_tensor(a))

    def _A_setup():
        B, S, D = (1, 2048, 512)
        ks = 4
        return {'q': _w((lambda *s: torch.randn(*s, dtype=torch.bfloat16) * 0.05)(B, S, D)), 'k': _w((lambda *s: torch.randn(*s, dtype=torch.bfloat16) * 0.8)(B, S, D)), 'v': _w((lambda *s: torch.randn(*s, dtype=torch.bfloat16) * 0.8)(B, S, D)), 'shift_k': _w((lambda *s: torch.randn(*s, dtype=torch.bfloat16) * 0.8)(D, ks) * 0.5), 'ssm_k': _w((lambda *s: torch.randn(*s, dtype=torch.bfloat16) * 1.6)(D, S) * (1.0 / S ** 0.5)), 'ssm_D': _w((lambda *s: torch.randn(*s, dtype=torch.bfloat16) * 0.8)(D))}
    _A_in = _A_setup()

    def _B_setup():
        B, S, D, F = (1, 2048, 512, 1792)
        Fh = F // 2
        return {'x': _w((lambda *s: torch.randn(*s, dtype=torch.bfloat16) * 0.05)(B, S, D)), 'w_in': _w((lambda *s: torch.randn(*s, dtype=torch.bfloat16) * 0.4)(D, 2 * Fh)), 'w_sp': _w(0.01 * (lambda *s: torch.randn(*s, dtype=torch.bfloat16) * 0.4)(S, S)), 'b_sp': _w(1.0 + 0.01 * (lambda *s: torch.randn(*s, dtype=torch.bfloat16) * 0.05)(S)), 'w_out': _w((lambda *s: torch.randn(*s, dtype=torch.bfloat16) * 0.05)(Fh, D))}
    _B_in = _B_setup()
    return {'A_q': _A_in['q'], 'A_k': _A_in['k'], 'A_v': _A_in['v'], 'A_shift_k': _A_in['shift_k'], 'A_ssm_k': _A_in['ssm_k'], 'A_ssm_D': _A_in['ssm_D'], 'B_x': _B_in['x'], 'B_w_in': _B_in['w_in'], 'B_w_sp': _B_in['w_sp'], 'B_b_sp': _B_in['b_sp'], 'B_w_out': _B_in['w_out']}

def reference(A_q, A_k, A_v, A_shift_k, A_ssm_k, A_ssm_D, B_x, B_w_in, B_w_sp, B_b_sp, B_w_out):

    def _A_ref(q, k, v, shift_k, ssm_k, ssm_D):
        B, S, D = q.shape
        ks = shift_k.shape[-1]
        k_pad = _pad(k, ((0, 0), (ks - 1, 0), (0, 0)))
        k_shift = torch.zeros_like(k)
        for t in range(ks):
            k_shift = k_shift + k_pad[:, t:t + S, :] * shift_k[:, ks - 1 - t][None, None, :]
        kv = k_shift * v
        L = 2 * S
        kv_pad = _pad(kv, ((0, 0), (0, S), (0, 0)))
        kf_pad = _pad(ssm_k, ((0, 0), (0, S)))
        kv_f = (lambda x, axes=(-2, -1): torch.fft.rfft2(x.float(), dim=axes))(kv_pad[:, None, :, :], axes=(1, 2))
        kf_f = (lambda x, axes=(-2, -1): torch.fft.rfft2(x.float(), dim=axes))(kf_pad[:, None, :], axes=(1, 2))
        kf_f = (lambda x, *d: x.permute(*d))(kf_f, 1, 2, 0)
        y_f = kv_f * kf_f[None, :, :, :]
        y = (lambda x, s, axes=(-2, -1): torch.fft.irfft2(x, s=s, dim=axes).to(torch.bfloat16))(y_f, (1, L), axes=(1, 2))[:, 0, :S, :]
        y = y + kv * ssm_D[None, None, :]
        return q * y

    def _B_ref(x, w_in, w_sp, b_sp, w_out):
        B, S, D = x.shape
        F = w_in.shape[-1]
        Fh = F // 2
        z = _gelu(torch.einsum('bsd,df->bsf', x, w_in))
        z1 = z[..., :Fh].clone()
        z2 = _layernorm(z[..., Fh:], axis=-1)
        g = torch.einsum('ts,bsf->btf', w_sp, z2) + b_sp[None, :, None]
        return torch.einsum('bsf,fd->bsd', z1 * g, w_out)
    x = A_q
    xn = _layernorm(x, axis=-1)
    return x + _A_ref(xn, A_k, A_v, A_shift_k, A_ssm_k, A_ssm_D) + _B_ref(xn, B_w_in, B_w_sp, B_b_sp, B_w_out)
```

```cpp
#include <cuda_runtime.h>
#include <cuda_bf16.h>
#include <cuda.h>
#include <stdint.h>

namespace {

constexpr int S_ = 2048, D_ = 512, F_ = 1792, FH_ = 896;
#define KV_ST 0
#define CONV_SKEW 0
#define NPRO 2
#define XS_K 7
constexpr int TILE_B = 28672;

constexpr int SM_TOTAL = 232448;
constexpr int OFF_X = 0;
constexpr int OFF_WR = 131072;
constexpr int G2_ST = 5, G2_STB = 30720;
constexpr int OFF_WO = 61440;
constexpr int OFF_WO6 = 153600;
constexpr int OFF_CV2 = 153600;
constexpr int OFF_P = 179072, OFF_P30 = 57344, OFF_P31 = 147456;
constexpr int OFF_XF = 211968, OFF_YF = 90112;
__host__ __device__ constexpr int hslot(int t) { return t == 0 || t == 3 || t == 7 ? 0 : t == 1 || t == 4 ? 28672 : t == 5 ? 61440 : 182272; }
constexpr int CV_K0 = 0, CV_K1 = 4128, CV_E = 8256, CV_O = 8256 + 2240, CV_CH = 8256 + 4480, CV_PAD = 192;
constexpr int OFF_CV = 205408;
constexpr int OFF_MISC = OFF_CV + 2 * CV_CH;
constexpr int OFF_CS = OFF_MISC;
constexpr int OFF_BAR = OFF_MISC + 960;
constexpr int OFF_EP = OFF_BAR + 8 * 75;
static_assert(OFF_EP + 8 <= SM_TOTAL, "smem");
enum { B_XF = 0, B_WF = 8, B_WE = 24, B_GF = 38, B_GE = 44, B_CS = 50, B_P1 = 51, B_CVF = 52, B_CVA = 54, B_WOF = 55, B_HE = 59,
       B_CVB = 63, B_FX = 64, B_FY = 65, B_EP = 66, B_CZ = 67, B_KV = 68, B_KE = 70, B_KP = 71, B_KS = 72, B_ZS = 73, B_ZI = 74, B_NUM = 75 };
__host__ __device__ constexpr int wslot(int k) { return OFF_WR + (k % 6) * 16384; }
constexpr int ZSLAB = 112 * 1024;

__device__ uint4 g_z2[8 * 16 * TILE_B / 16];
__device__ uint4 g_h[16 * 8 * TILE_B / 16];
__device__ uint4 g_kv[512 * 4096 / 16];
__device__ uint4 g_y[512 * 4096 / 16];
__device__ uint4 g_st[16 * 7 * 128];
__device__ uint4 g_xs[2048];
__device__ uint4 g_cz[448];
__device__ uint2 g_cs[896];
__device__ uint32_t g_cnt[2 * 32];
__device__ uint32_t g_fh[16 * 16 * 8];
__device__ uint32_t g_fk[8 * 16 * 8];
__device__ uint32_t g_fy[8 * 32 * 8];
__device__ uint32_t g_epoch;
#define STAMP(i) do {} while (0)
#define STAMPG(i) do {} while (0)

struct Params {
  const __nv_bfloat16 *x, *k, *v, *shift, *ssm_k, *ssm_D, *w_in, *w_sp, *b_sp;
};

__device__ __forceinline__ void fail() { asm volatile("st.global.u32 [%0], %1;" ::"l"(0ULL), "r"(0) : "memory"); }
__device__ __forceinline__ uint32_t smem_u32(const void* p) { return (uint32_t)__cvta_generic_to_shared(p); }
__device__ __forceinline__ void mbar_init(uint32_t bar, int cnt) { asm volatile("mbarrier.init.shared::cta.b64 [%0], %1;" ::"r"(bar), "r"(cnt)); }
__device__ __forceinline__ void mbar_expect_tx(uint32_t bar, uint32_t bytes) { asm volatile("mbarrier.arrive.expect_tx.shared::cta.b64 _, [%0], %1;" ::"r"(bar), "r"(bytes) : "memory"); }
__device__ __forceinline__ void mbar_arrive(uint32_t bar) { asm volatile("mbarrier.arrive.shared::cta.b64 _, [%0];" ::"r"(bar) : "memory"); }
__device__ __forceinline__ void mbar_wait(uint32_t bar, uint32_t par) {
  asm volatile("{\n.reg .pred p;\n.reg .b32 n;\n"
               "mbarrier.try_wait.parity.shared::cta.b64 p, [%0], %1;\n@p bra.uni DONE;\nmov.b32 n, 0;\n"
               "LOOP:\nmbarrier.try_wait.parity.shared::cta.b64 p, [%0], %1;\n@p bra.uni DONE;\n"
               "add.u32 n, n, 1;\nsetp.lt.u32 p, n, 0x100000;\n@p bra.uni LOOP;\n"
               "st.global.u32 [%2], n;\nDONE:\n}" ::"r"(bar), "r"(par), "l"(0ULL) : "memory");
}
__device__ __forceinline__ void tma2d(uint32_t dst, const CUtensorMap* m, int c0, int c1, uint32_t bar) {
  asm volatile("cp.async.bulk.tensor.2d.shared::cluster.global.mbarrier::complete_tx::bytes [%0], [%1, {%3, %4}], [%2];" ::"r"(dst), "l"(m), "r"(bar), "r"(c0), "r"(c1) : "memory");
}
__device__ __forceinline__ void tma3d(uint32_t dst, const CUtensorMap* m, int c0, int c1, int c2, uint32_t bar) {
  asm volatile("cp.async.bulk.tensor.3d.shared::cluster.global.mbarrier::complete_tx::bytes [%0], [%1, {%3, %4, %5}], [%2];" ::"r"(dst), "l"(m), "r"(bar), "r"(c0), "r"(c1), "r"(c2) : "memory");
}
__device__ __forceinline__ void tma2d_pf(const CUtensorMap* m, int c0, int c1) {
  asm volatile("cp.async.bulk.prefetch.tensor.2d.L2.global.tile [%0, {%1, %2}];" ::"l"(m), "r"(c0), "r"(c1) : "memory");
}
__device__ __forceinline__ void tma2d_st(const CUtensorMap* m, int c0, int c1, uint32_t src) {
  asm volatile("cp.async.bulk.tensor.2d.global.shared::cta.bulk_group [%0, {%1, %2}], [%3];" ::"l"(m), "r"(c0), "r"(c1), "r"(src) : "memory");
}
__device__ __forceinline__ void bulk_g2s(uint32_t dst, const void* src, uint32_t bytes, uint32_t bar) {
  asm volatile("cp.async.bulk.shared::cluster.global.mbarrier::complete_tx::bytes [%0], [%1], %2, [%3];" ::"r"(dst), "l"(src), "r"(bytes), "r"(bar) : "memory");
}
__device__ __forceinline__ void bulk_s2g(void* dst, uint32_t src, uint32_t bytes) {
  asm volatile("cp.async.bulk.global.shared::cta.bulk_group [%0], [%1], %2;" ::"l"(dst), "r"(src), "r"(bytes) : "memory");
}
__device__ __forceinline__ void bulk_commit() { asm volatile("cp.async.bulk.commit_group;" ::: "memory"); }
template <int N> __device__ __forceinline__ void bulk_wait() { asm volatile("cp.async.bulk.wait_group %0;" ::"n"(N) : "memory"); }
__device__ __forceinline__ void bulk_pf(const void* src, uint32_t bytes) { asm volatile("cp.async.bulk.prefetch.L2.global [%0], %1;" ::"l"(src), "r"(bytes) : "memory"); }
__device__ __forceinline__ void fence_gpu() { asm volatile("fence.acq_rel.gpu;" ::: "memory"); }
__device__ __forceinline__ void st_flag(uint32_t* p, uint32_t v) {
  asm volatile("st.relaxed.gpu.global.v4.u32 [%0], {%1,%1,%1,%1};\nst.relaxed.gpu.global.v4.u32 [%0+16], {%1,%1,%1,%1};" ::"l"(p), "r"(v) : "memory");
}
__device__ __forceinline__ void wg_fence() { asm volatile("wgmma.fence.sync.aligned;" ::: "memory"); }
__device__ __forceinline__ void wg_commit() { asm volatile("wgmma.commit_group.sync.aligned;" ::: "memory"); }
template <int N> __device__ __forceinline__ void wg_wait() { asm volatile("wgmma.wait_group.sync.aligned %0;" ::"n"(N) : "memory"); }
__device__ __forceinline__ uint32_t dlo(uint32_t addr, uint32_t lbo) { return ((addr & 0x3FFFF) >> 4) | ((lbo >> 4) << 16); }
__host__ __device__ constexpr uint32_t dhi(uint32_t sbo, uint32_t swz) { return (sbo >> 4) | (swz << 30); }
__device__ __forceinline__ void bar_sync(int id, int n) { asm volatile("bar.sync %0, %1;" ::"r"(id), "r"(n) : "memory"); }
__device__ __forceinline__ void fence_async_smem() { asm volatile("fence.proxy.async.shared::cta;" ::: "memory"); }
__device__ __forceinline__ void fence_async_glob() { asm volatile("fence.proxy.async.global;" ::: "memory"); }
__device__ __forceinline__ uint32_t ld_acq(const uint32_t* p) { uint32_t v; asm volatile("ld.acquire.gpu.global.u32 %0, [%1];" : "=r"(v) : "l"(p) : "memory"); return v; }
__device__ __forceinline__ uint32_t ld_rlx(const uint32_t* p) { uint32_t v; asm volatile("ld.relaxed.gpu.global.u32 %0, [%1];" : "=r"(v) : "l"(p) : "memory"); return v; }
__device__ __forceinline__ void st_rlx(uint32_t* p, uint32_t v) { asm volatile("st.relaxed.gpu.global.u32 [%0], %1;" ::"l"(p), "r"(v) : "memory"); }
__device__ __forceinline__ uint4 ld_rlx128(const uint4* p) {
  uint4 v;
  asm volatile("{\n.reg .b128 r;\n.reg .b64 a, b;\nld.relaxed.gpu.global.b128 r, [%4];\nmov.b128 {a, b}, r;\nmov.b64 {%0, %1}, a;\nmov.b64 {%2, %3}, b;\n}"
               : "=r"(v.x), "=r"(v.y), "=r"(v.z), "=r"(v.w) : "l"(p) : "memory");
  return v;
}
__device__ __forceinline__ void st_rlx128(uint4* p, uint4 v) {
  asm volatile("{\n.reg .b128 r;\n.reg .b64 a, b;\nmov.b64 a, {%1, %2};\nmov.b64 b, {%3, %4};\nmov.b128 r, {a, b};\nst.relaxed.gpu.global.b128 [%0], r;\n}"
               ::"l"(p), "r"(v.x), "r"(v.y), "r"(v.z), "r"(v.w) : "memory");
}
__device__ __forceinline__ uint2 ld_rlx64(const uint2* p) { unsigned long long v; asm volatile("ld.relaxed.gpu.global.b64 %0, [%1];" : "=l"(v) : "l"(p) : "memory"); return make_uint2((uint32_t)v, (uint32_t)(v >> 32)); }
__device__ __forceinline__ void st_rlx64(uint2* p, uint2 v) { unsigned long long w = (unsigned long long)v.x | ((unsigned long long)v.y << 32); asm volatile("st.relaxed.gpu.global.b64 [%0], %1;" ::"l"(p), "l"(w) : "memory"); }
__device__ __forceinline__ uint4 ldg128(const void* p) { uint4 v; asm volatile("ld.global.nc.L1::no_allocate.v4.u32 {%0,%1,%2,%3}, [%4];" : "=r"(v.x), "=r"(v.y), "=r"(v.z), "=r"(v.w) : "l"(p)); return v; }
__device__ __forceinline__ uint2 ldg64(const void* p) { uint2 v; asm volatile("ld.global.nc.L1::no_allocate.v2.u32 {%0,%1}, [%2];" : "=r"(v.x), "=r"(v.y) : "l"(p)); return v; }
__device__ __forceinline__ uint32_t ldg32(const void* p) { uint32_t v; asm volatile("ld.global.nc.L1::no_allocate.u32 %0, [%1];" : "=r"(v) : "l"(p)); return v; }
__device__ __forceinline__ uint32_t ldg16(const void* p) { unsigned short v; asm volatile("ld.global.nc.u16 %0, [%1];" : "=h"(v) : "l"(p)); return v; }
__device__ __forceinline__ uint32_t lds32(uint32_t a) { uint32_t v; asm volatile("ld.shared.b32 %0, [%1];" : "=r"(v) : "r"(a)); return v; }
__device__ __forceinline__ float2 lds64f(uint32_t a) { float2 v; asm volatile("ld.shared.v2.f32 {%0,%1}, [%2];" : "=f"(v.x), "=f"(v.y) : "r"(a)); return v; }
__device__ __forceinline__ uint4 lds128(uint32_t a) { uint4 v; asm volatile("ld.shared.v4.b32 {%0,%1,%2,%3}, [%4];" : "=r"(v.x), "=r"(v.y), "=r"(v.z), "=r"(v.w) : "r"(a) : "memory"); return v; }
__device__ __forceinline__ void sts128(uint32_t a, uint4 v) { asm volatile("st.shared.v4.b32 [%0], {%1,%2,%3,%4};" ::"r"(a), "r"(v.x), "r"(v.y), "r"(v.z), "r"(v.w) : "memory"); }
__device__ __forceinline__ void ldsm4(uint32_t a, uint32_t (&r)[4]) { asm volatile("ldmatrix.sync.aligned.m8n8.x4.shared.b16 {%0,%1,%2,%3}, [%4];" : "=r"(r[0]), "=r"(r[1]), "=r"(r[2]), "=r"(r[3]) : "r"(a) : "memory"); }
__device__ __forceinline__ void ldsm4t(uint32_t a, uint32_t (&r)[4]) { asm volatile("ldmatrix.sync.aligned.m8n8.x4.trans.shared.b16 {%0,%1,%2,%3}, [%4];" : "=r"(r[0]), "=r"(r[1]), "=r"(r[2]), "=r"(r[3]) : "r"(a) : "memory"); }
__device__ __forceinline__ void stsm4(uint32_t a, uint32_t r0, uint32_t r1, uint32_t r2, uint32_t r3) { asm volatile("stmatrix.sync.aligned.m8n8.x4.shared.b16 [%0], {%1,%2,%3,%4};" ::"r"(a), "r"(r0), "r"(r1), "r"(r2), "r"(r3) : "memory"); }
__device__ __forceinline__ void stsm4t(uint32_t a, uint32_t r0, uint32_t r1, uint32_t r2, uint32_t r3) { asm volatile("stmatrix.sync.aligned.m8n8.x4.trans.shared.b16 [%0], {%1,%2,%3,%4};" ::"r"(a), "r"(r0), "r"(r1), "r"(r2), "r"(r3) : "memory"); }
__device__ __forceinline__ uint32_t pack2(float lo, float hi) { uint32_t r; asm("cvt.rn.bf16x2.f32 %0, %1, %2;" : "=r"(r) : "f"(hi), "f"(lo)); return r; }
__device__ __forceinline__ float blo(uint32_t v) { return __uint_as_float(v << 16); }
__device__ __forceinline__ float bhi(uint32_t v) { return __uint_as_float(v & 0xffff0000u); }
__device__ __forceinline__ uint32_t bmul(uint32_t a, uint32_t b) { uint32_t r; asm("mul.rn.bf16x2 %0, %1, %2;" : "=r"(r) : "r"(a), "r"(b)); return r; }
__device__ __forceinline__ uint32_t badd(uint32_t a, uint32_t b) { uint32_t r; asm("add.rn.bf16x2 %0, %1, %2;" : "=r"(r) : "r"(a), "r"(b)); return r; }
__device__ __forceinline__ uint32_t bfma(uint32_t a, uint32_t b, uint32_t c) { uint32_t r; asm("fma.rn.bf16x2 %0, %1, %2, %3;" : "=r"(r) : "r"(a), "r"(b), "r"(c)); return r; }
__device__ __forceinline__ void mma16816(float (&d)[4], uint32_t a0, uint32_t a1, uint32_t a2, uint32_t a3, uint32_t b0, uint32_t b1) {
  asm volatile("mma.sync.aligned.m16n8k16.row.col.f32.bf16.bf16.f32 {%0,%1,%2,%3}, {%4,%5,%6,%7}, {%8,%9}, {%0,%1,%2,%3};"
               : "+f"(d[0]), "+f"(d[1]), "+f"(d[2]), "+f"(d[3]) : "r"(a0), "r"(a1), "r"(a2), "r"(a3), "r"(b0), "r"(b1));
}
__device__ __forceinline__ float rsq(float x) { float y; asm("rsqrt.approx.ftz.f32 %0, %1;" : "=f"(y) : "f"(x)); return y; }
__device__ __forceinline__ float tanh_(float x) { float y; asm("tanh.approx.f32 %0, %1;" : "=f"(y) : "f"(x)); return y; }
__device__ __forceinline__ float qsum(float v) { v += __shfl_xor_sync(~0u, v, 1); v += __shfl_xor_sync(~0u, v, 2); return v; }
template <int N> __device__ __forceinline__ void zero_acc(float (&d)[N]) {
#pragma unroll
  for (int i = 0; i < N; i++) asm volatile("mov.b32 %0, 0;" : "=f"(d[i]));
}
template <int I> struct IC { static constexpr int v = I; };
template <int B, int E, typename F> __device__ __forceinline__ void sfor(F f) { if constexpr (B < E) { f(IC<B>{}); sfor<B + 1, E>(f); } }

template <int NPER> __device__ __forceinline__ void poll_flags(const uint32_t* base, int n, uint32_t tag, int lane) {
  uint32_t it = 0;
  while (true) {
    bool ok = true;
#pragma unroll
    for (int i = 0; i < NPER; i++) if (lane + 32 * i < n) ok &= (ld_rlx(base + (lane + 32 * i) * 8) == tag);
    if (__all_sync(~0u, ok)) break;
    if (++it > (1u << 20)) fail();
  }
  asm volatile("fence.acquire.gpu;" ::: "memory");
  __syncwarp();
  fence_async_glob();
}
__device__ __forceinline__ void wgmma_ss_n112(float (&d)[56], uint32_t al, uint32_t ah, uint32_t bl, uint32_t bh) {
  asm volatile("{\n.reg .b64 da, db;\nmov.b64 da, {%56, %57};\nmov.b64 db, {%58, %59};\n"
    "wgmma.mma_async.sync.aligned.m64n112k16.f32.bf16.bf16 {%0, %1, %2, %3, %4, %5, %6, %7, %8, %9, %10, %11, %12, %13, %14, %15, %16, %17, %18, %19, %20, %21, %22, %23, %24, %25, %26, %27, %28, %29, %30, %31, %32, %33, %34, %35, %36, %37, %38, %39, %40, %41, %42, %43, %44, %45, %46, %47, %48, %49, %50, %51, %52, %53, %54, %55}, da, db, 1, 1, 1, 0, 1;\n}\n"
    : "+f"(d[0]), "+f"(d[1]), "+f"(d[2]), "+f"(d[3]), "+f"(d[4]), "+f"(d[5]), "+f"(d[6]), "+f"(d[7]), "+f"(d[8]), "+f"(d[9]), "+f"(d[10]), "+f"(d[11]), "+f"(d[12]), "+f"(d[13]), "+f"(d[14]), "+f"(d[15]), "+f"(d[16]), "+f"(d[17]), "+f"(d[18]), "+f"(d[19]), "+f"(d[20]), "+f"(d[21]), "+f"(d[22]), "+f"(d[23]), "+f"(d[24]), "+f"(d[25]), "+f"(d[26]), "+f"(d[27]), "+f"(d[28]), "+f"(d[29]), "+f"(d[30]), "+f"(d[31]), "+f"(d[32]), "+f"(d[33]), "+f"(d[34]), "+f"(d[35]), "+f"(d[36]), "+f"(d[37]), "+f"(d[38]), "+f"(d[39]), "+f"(d[40]), "+f"(d[41]), "+f"(d[42]), "+f"(d[43]), "+f"(d[44]), "+f"(d[45]), "+f"(d[46]), "+f"(d[47]), "+f"(d[48]), "+f"(d[49]), "+f"(d[50]), "+f"(d[51]), "+f"(d[52]), "+f"(d[53]), "+f"(d[54]), "+f"(d[55])
    : "r"(al), "r"(ah), "r"(bl), "r"(bh));
}
__device__ __forceinline__ void wgmma_ss_n128(float (&d)[64], uint32_t al, uint32_t ah, uint32_t bl, uint32_t bh) {
  asm volatile("{\n.reg .b64 da, db;\nmov.b64 da, {%64, %65};\nmov.b64 db, {%66, %67};\n"
    "wgmma.mma_async.sync.aligned.m64n128k16.f32.bf16.bf16 {%0, %1, %2, %3, %4, %5, %6, %7, %8, %9, %10, %11, %12, %13, %14, %15, %16, %17, %18, %19, %20, %21, %22, %23, %24, %25, %26, %27, %28, %29, %30, %31, %32, %33, %34, %35, %36, %37, %38, %39, %40, %41, %42, %43, %44, %45, %46, %47, %48, %49, %50, %51, %52, %53, %54, %55, %56, %57, %58, %59, %60, %61, %62, %63}, da, db, 1, 1, 1, 0, 1;\n}\n"
    : "+f"(d[0]), "+f"(d[1]), "+f"(d[2]), "+f"(d[3]), "+f"(d[4]), "+f"(d[5]), "+f"(d[6]), "+f"(d[7]), "+f"(d[8]), "+f"(d[9]), "+f"(d[10]), "+f"(d[11]), "+f"(d[12]), "+f"(d[13]), "+f"(d[14]), "+f"(d[15]), "+f"(d[16]), "+f"(d[17]), "+f"(d[18]), "+f"(d[19]), "+f"(d[20]), "+f"(d[21]), "+f"(d[22]), "+f"(d[23]), "+f"(d[24]), "+f"(d[25]), "+f"(d[26]), "+f"(d[27]), "+f"(d[28]), "+f"(d[29]), "+f"(d[30]), "+f"(d[31]), "+f"(d[32]), "+f"(d[33]), "+f"(d[34]), "+f"(d[35]), "+f"(d[36]), "+f"(d[37]), "+f"(d[38]), "+f"(d[39]), "+f"(d[40]), "+f"(d[41]), "+f"(d[42]), "+f"(d[43]), "+f"(d[44]), "+f"(d[45]), "+f"(d[46]), "+f"(d[47]), "+f"(d[48]), "+f"(d[49]), "+f"(d[50]), "+f"(d[51]), "+f"(d[52]), "+f"(d[53]), "+f"(d[54]), "+f"(d[55]), "+f"(d[56]), "+f"(d[57]), "+f"(d[58]), "+f"(d[59]), "+f"(d[60]), "+f"(d[61]), "+f"(d[62]), "+f"(d[63])
    : "r"(al), "r"(ah), "r"(bl), "r"(bh));
}
__device__ __forceinline__ void wgmma_ss_n64(float (&d)[32], uint32_t al, uint32_t ah, uint32_t bl, uint32_t bh) {
  asm volatile("{\n.reg .b64 da, db;\nmov.b64 da, {%32, %33};\nmov.b64 db, {%34, %35};\n"
    "wgmma.mma_async.sync.aligned.m64n64k16.f32.bf16.bf16 {%0, %1, %2, %3, %4, %5, %6, %7, %8, %9, %10, %11, %12, %13, %14, %15, %16, %17, %18, %19, %20, %21, %22, %23, %24, %25, %26, %27, %28, %29, %30, %31}, da, db, 1, 1, 1, 0, 1;\n}\n"
    : "+f"(d[0]), "+f"(d[1]), "+f"(d[2]), "+f"(d[3]), "+f"(d[4]), "+f"(d[5]), "+f"(d[6]), "+f"(d[7]), "+f"(d[8]), "+f"(d[9]), "+f"(d[10]), "+f"(d[11]), "+f"(d[12]), "+f"(d[13]), "+f"(d[14]), "+f"(d[15]), "+f"(d[16]), "+f"(d[17]), "+f"(d[18]), "+f"(d[19]), "+f"(d[20]), "+f"(d[21]), "+f"(d[22]), "+f"(d[23]), "+f"(d[24]), "+f"(d[25]), "+f"(d[26]), "+f"(d[27]), "+f"(d[28]), "+f"(d[29]), "+f"(d[30]), "+f"(d[31])
    : "r"(al), "r"(ah), "r"(bl), "r"(bh));
}
template <int N> __device__ __forceinline__ void wgmma_cv(float (&d)[64], uint32_t a0, uint32_t a1, uint32_t a2, uint32_t a3, uint32_t bl);
template <> __device__ __forceinline__ void wgmma_cv<16>(float (&d)[64], uint32_t a0, uint32_t a1, uint32_t a2, uint32_t a3, uint32_t bl) {
  asm volatile("{\n.reg .b64 db;\nmov.b64 db, {%12, 8};\n"
    "wgmma.mma_async.sync.aligned.m64n16k16.f32.bf16.bf16 {%0, %1, %2, %3, %4, %5, %6, %7}, {%8, %9, %10, %11}, db, 1, 1, 1, 0;\n}\n"
    : "+f"(d[56]), "+f"(d[57]), "+f"(d[58]), "+f"(d[59]), "+f"(d[60]), "+f"(d[61]), "+f"(d[62]), "+f"(d[63])
    : "r"(a0), "r"(a1), "r"(a2), "r"(a3), "r"(bl));
}
template <> __device__ __forceinline__ void wgmma_cv<32>(float (&d)[64], uint32_t a0, uint32_t a1, uint32_t a2, uint32_t a3, uint32_t bl) {
  asm volatile("{\n.reg .b64 db;\nmov.b64 db, {%20, 8};\n"
    "wgmma.mma_async.sync.aligned.m64n32k16.f32.bf16.bf16 {%0, %1, %2, %3, %4, %5, %6, %7, %8, %9, %10, %11, %12, %13, %14, %15}, {%16, %17, %18, %19}, db, 1, 1, 1, 0;\n}\n"
    : "+f"(d[48]), "+f"(d[49]), "+f"(d[50]), "+f"(d[51]), "+f"(d[52]), "+f"(d[53]), "+f"(d[54]), "+f"(d[55]), "+f"(d[56]), "+f"(d[57]), "+f"(d[58]), "+f"(d[59]), "+f"(d[60]), "+f"(d[61]), "+f"(d[62]), "+f"(d[63])
    : "r"(a0), "r"(a1), "r"(a2), "r"(a3), "r"(bl));
}
template <> __device__ __forceinline__ void wgmma_cv<48>(float (&d)[64], uint32_t a0, uint32_t a1, uint32_t a2, uint32_t a3, uint32_t bl) {
  asm volatile("{\n.reg .b64 db;\nmov.b64 db, {%28, 8};\n"
    "wgmma.mma_async.sync.aligned.m64n48k16.f32.bf16.bf16 {%0, %1, %2, %3, %4, %5, %6, %7, %8, %9, %10, %11, %12, %13, %14, %15, %16, %17, %18, %19, %20, %21, %22, %23}, {%24, %25, %26, %27}, db, 1, 1, 1, 0;\n}\n"
    : "+f"(d[40]), "+f"(d[41]), "+f"(d[42]), "+f"(d[43]), "+f"(d[44]), "+f"(d[45]), "+f"(d[46]), "+f"(d[47]), "+f"(d[48]), "+f"(d[49]), "+f"(d[50]), "+f"(d[51]), "+f"(d[52]), "+f"(d[53]), "+f"(d[54]), "+f"(d[55]), "+f"(d[56]), "+f"(d[57]), "+f"(d[58]), "+f"(d[59]), "+f"(d[60]), "+f"(d[61]), "+f"(d[62]), "+f"(d[63])
    : "r"(a0), "r"(a1), "r"(a2), "r"(a3), "r"(bl));
}
template <> __device__ __forceinline__ void wgmma_cv<64>(float (&d)[64], uint32_t a0, uint32_t a1, uint32_t a2, uint32_t a3, uint32_t bl) {
  asm volatile("{\n.reg .b64 db;\nmov.b64 db, {%36, 8};\n"
    "wgmma.mma_async.sync.aligned.m64n64k16.f32.bf16.bf16 {%0, %1, %2, %3, %4, %5, %6, %7, %8, %9, %10, %11, %12, %13, %14, %15, %16, %17, %18, %19, %20, %21, %22, %23, %24, %25, %26, %27, %28, %29, %30, %31}, {%32, %33, %34, %35}, db, 1, 1, 1, 0;\n}\n"
    : "+f"(d[32]), "+f"(d[33]), "+f"(d[34]), "+f"(d[35]), "+f"(d[36]), "+f"(d[37]), "+f"(d[38]), "+f"(d[39]), "+f"(d[40]), "+f"(d[41]), "+f"(d[42]), "+f"(d[43]), "+f"(d[44]), "+f"(d[45]), "+f"(d[46]), "+f"(d[47]), "+f"(d[48]), "+f"(d[49]), "+f"(d[50]), "+f"(d[51]), "+f"(d[52]), "+f"(d[53]), "+f"(d[54]), "+f"(d[55]), "+f"(d[56]), "+f"(d[57]), "+f"(d[58]), "+f"(d[59]), "+f"(d[60]), "+f"(d[61]), "+f"(d[62]), "+f"(d[63])
    : "r"(a0), "r"(a1), "r"(a2), "r"(a3), "r"(bl));
}
template <> __device__ __forceinline__ void wgmma_cv<80>(float (&d)[64], uint32_t a0, uint32_t a1, uint32_t a2, uint32_t a3, uint32_t bl) {
  asm volatile("{\n.reg .b64 db;\nmov.b64 db, {%44, 8};\n"
    "wgmma.mma_async.sync.aligned.m64n80k16.f32.bf16.bf16 {%0, %1, %2, %3, %4, %5, %6, %7, %8, %9, %10, %11, %12, %13, %14, %15, %16, %17, %18, %19, %20, %21, %22, %23, %24, %25, %26, %27, %28, %29, %30, %31, %32, %33, %34, %35, %36, %37, %38, %39}, {%40, %41, %42, %43}, db, 1, 1, 1, 0;\n}\n"
    : "+f"(d[24]), "+f"(d[25]), "+f"(d[26]), "+f"(d[27]), "+f"(d[28]), "+f"(d[29]), "+f"(d[30]), "+f"(d[31]), "+f"(d[32]), "+f"(d[33]), "+f"(d[34]), "+f"(d[35]), "+f"(d[36]), "+f"(d[37]), "+f"(d[38]), "+f"(d[39]), "+f"(d[40]), "+f"(d[41]), "+f"(d[42]), "+f"(d[43]), "+f"(d[44]), "+f"(d[45]), "+f"(d[46]), "+f"(d[47]), "+f"(d[48]), "+f"(d[49]), "+f"(d[50]), "+f"(d[51]), "+f"(d[52]), "+f"(d[53]), "+f"(d[54]), "+f"(d[55]), "+f"(d[56]), "+f"(d[57]), "+f"(d[58]), "+f"(d[59]), "+f"(d[60]), "+f"(d[61]), "+f"(d[62]), "+f"(d[63])
    : "r"(a0), "r"(a1), "r"(a2), "r"(a3), "r"(bl));
}
template <> __device__ __forceinline__ void wgmma_cv<96>(float (&d)[64], uint32_t a0, uint32_t a1, uint32_t a2, uint32_t a3, uint32_t bl) {
  asm volatile("{\n.reg .b64 db;\nmov.b64 db, {%52, 8};\n"
    "wgmma.mma_async.sync.aligned.m64n96k16.f32.bf16.bf16 {%0, %1, %2, %3, %4, %5, %6, %7, %8, %9, %10, %11, %12, %13, %14, %15, %16, %17, %18, %19, %20, %21, %22, %23, %24, %25, %26, %27, %28, %29, %30, %31, %32, %33, %34, %35, %36, %37, %38, %39, %40, %41, %42, %43, %44, %45, %46, %47}, {%48, %49, %50, %51}, db, 1, 1, 1, 0;\n}\n"
    : "+f"(d[16]), "+f"(d[17]), "+f"(d[18]), "+f"(d[19]), "+f"(d[20]), "+f"(d[21]), "+f"(d[22]), "+f"(d[23]), "+f"(d[24]), "+f"(d[25]), "+f"(d[26]), "+f"(d[27]), "+f"(d[28]), "+f"(d[29]), "+f"(d[30]), "+f"(d[31]), "+f"(d[32]), "+f"(d[33]), "+f"(d[34]), "+f"(d[35]), "+f"(d[36]), "+f"(d[37]), "+f"(d[38]), "+f"(d[39]), "+f"(d[40]), "+f"(d[41]), "+f"(d[42]), "+f"(d[43]), "+f"(d[44]), "+f"(d[45]), "+f"(d[46]), "+f"(d[47]), "+f"(d[48]), "+f"(d[49]), "+f"(d[50]), "+f"(d[51]), "+f"(d[52]), "+f"(d[53]), "+f"(d[54]), "+f"(d[55]), "+f"(d[56]), "+f"(d[57]), "+f"(d[58]), "+f"(d[59]), "+f"(d[60]), "+f"(d[61]), "+f"(d[62]), "+f"(d[63])
    : "r"(a0), "r"(a1), "r"(a2), "r"(a3), "r"(bl));
}
template <> __device__ __forceinline__ void wgmma_cv<112>(float (&d)[64], uint32_t a0, uint32_t a1, uint32_t a2, uint32_t a3, uint32_t bl) {
  asm volatile("{\n.reg .b64 db;\nmov.b64 db, {%60, 8};\n"
    "wgmma.mma_async.sync.aligned.m64n112k16.f32.bf16.bf16 {%0, %1, %2, %3, %4, %5, %6, %7, %8, %9, %10, %11, %12, %13, %14, %15, %16, %17, %18, %19, %20, %21, %22, %23, %24, %25, %26, %27, %28, %29, %30, %31, %32, %33, %34, %35, %36, %37, %38, %39, %40, %41, %42, %43, %44, %45, %46, %47, %48, %49, %50, %51, %52, %53, %54, %55}, {%56, %57, %58, %59}, db, 1, 1, 1, 0;\n}\n"
    : "+f"(d[8]), "+f"(d[9]), "+f"(d[10]), "+f"(d[11]), "+f"(d[12]), "+f"(d[13]), "+f"(d[14]), "+f"(d[15]), "+f"(d[16]), "+f"(d[17]), "+f"(d[18]), "+f"(d[19]), "+f"(d[20]), "+f"(d[21]), "+f"(d[22]), "+f"(d[23]), "+f"(d[24]), "+f"(d[25]), "+f"(d[26]), "+f"(d[27]), "+f"(d[28]), "+f"(d[29]), "+f"(d[30]), "+f"(d[31]), "+f"(d[32]), "+f"(d[33]), "+f"(d[34]), "+f"(d[35]), "+f"(d[36]), "+f"(d[37]), "+f"(d[38]), "+f"(d[39]), "+f"(d[40]), "+f"(d[41]), "+f"(d[42]), "+f"(d[43]), "+f"(d[44]), "+f"(d[45]), "+f"(d[46]), "+f"(d[47]), "+f"(d[48]), "+f"(d[49]), "+f"(d[50]), "+f"(d[51]), "+f"(d[52]), "+f"(d[53]), "+f"(d[54]), "+f"(d[55]), "+f"(d[56]), "+f"(d[57]), "+f"(d[58]), "+f"(d[59]), "+f"(d[60]), "+f"(d[61]), "+f"(d[62]), "+f"(d[63])
    : "r"(a0), "r"(a1), "r"(a2), "r"(a3), "r"(bl));
}
template <> __device__ __forceinline__ void wgmma_cv<128>(float (&d)[64], uint32_t a0, uint32_t a1, uint32_t a2, uint32_t a3, uint32_t bl) {
  asm volatile("{\n.reg .b64 db;\nmov.b64 db, {%68, 8};\n"
    "wgmma.mma_async.sync.aligned.m64n128k16.f32.bf16.bf16 {%0, %1, %2, %3, %4, %5, %6, %7, %8, %9, %10, %11, %12, %13, %14, %15, %16, %17, %18, %19, %20, %21, %22, %23, %24, %25, %26, %27, %28, %29, %30, %31, %32, %33, %34, %35, %36, %37, %38, %39, %40, %41, %42, %43, %44, %45, %46, %47, %48, %49, %50, %51, %52, %53, %54, %55, %56, %57, %58, %59, %60, %61, %62, %63}, {%64, %65, %66, %67}, db, 1, 1, 1, 0;\n}\n"
    : "+f"(d[0]), "+f"(d[1]), "+f"(d[2]), "+f"(d[3]), "+f"(d[4]), "+f"(d[5]), "+f"(d[6]), "+f"(d[7]), "+f"(d[8]), "+f"(d[9]), "+f"(d[10]), "+f"(d[11]), "+f"(d[12]), "+f"(d[13]), "+f"(d[14]), "+f"(d[15]), "+f"(d[16]), "+f"(d[17]), "+f"(d[18]), "+f"(d[19]), "+f"(d[20]), "+f"(d[21]), "+f"(d[22]), "+f"(d[23]), "+f"(d[24]), "+f"(d[25]), "+f"(d[26]), "+f"(d[27]), "+f"(d[28]), "+f"(d[29]), "+f"(d[30]), "+f"(d[31]), "+f"(d[32]), "+f"(d[33]), "+f"(d[34]), "+f"(d[35]), "+f"(d[36]), "+f"(d[37]), "+f"(d[38]), "+f"(d[39]), "+f"(d[40]), "+f"(d[41]), "+f"(d[42]), "+f"(d[43]), "+f"(d[44]), "+f"(d[45]), "+f"(d[46]), "+f"(d[47]), "+f"(d[48]), "+f"(d[49]), "+f"(d[50]), "+f"(d[51]), "+f"(d[52]), "+f"(d[53]), "+f"(d[54]), "+f"(d[55]), "+f"(d[56]), "+f"(d[57]), "+f"(d[58]), "+f"(d[59]), "+f"(d[60]), "+f"(d[61]), "+f"(d[62]), "+f"(d[63])
    : "r"(a0), "r"(a1), "r"(a2), "r"(a3), "r"(bl));
}

struct RowC { float nmu, a, b; };
__device__ __forceinline__ float gelu_f(float acc, float cs, const RowC& c) {
  float t = fmaf(c.nmu, cs, acc);
  float u = t * fmaf(t * t, c.b, c.a);
  return fmaf(t, tanh_(u), t);
}

__device__ __forceinline__ void conv_mma(uint32_t cv, uint32_t pw, int w, int lane) {
  const int g = lane >> 2, tq = lane & 3;
  float d[64];
  zero_acc(d);
  const uint32_t abase = cv + ((g & 1) ? (CV_K0 + 2 * (16 + 16 * w + g - 2 * tq - 1)) : (CV_K1 + 2 * (16 + 16 * w + g - 2 * tq)));
  const uint32_t dbase = dlo(cv + CV_E + CV_PAD, CV_O - CV_E);
  const int mi = lane >> 3, rr = lane & 7;
  const uint32_t paddr = pw + 16 * ((2 * ((mi >> 1) * 8 + rr + w) + (mi & 1)) ^ (((rr + w) >> 2) & 1));
  uint32_t a[32][3];
  auto loadA = [&](auto bi) {
    constexpr int b = decltype(bi)::v;
    if constexpr (b < 8) {
#pragma unroll
      for (int s = 0; s < 4; s++) {
        const int st = 4 * b + s;
        a[st][0] = lds32(abase + 128 * st); a[st][1] = lds32(abase + 128 * st + 16); a[st][2] = lds32(abase + 128 * st - 16);
      }
    }
  };
  loadA(IC<0>{});
  sfor<0, 8>([&](auto ii) {
    constexpr int b = decltype(ii)::v;
    wg_fence();
    sfor<0, 4>([&](auto ss) {
      constexpr int st = 4 * b + decltype(ss)::v;
      wgmma_cv<128 - 16 * b>(d, a[st][0], a[st][1], a[st][2], a[st][0], dbase - (4 * st - 16 * b));
    });
    wg_commit();
    loadA(IC<b + 1>{});
    if constexpr (b > 0) {
      constexpr int i = 2 * (b - 1);
      stsm4t(paddr + i * 256, pack2(d[4 * i], d[4 * i + 1]), pack2(d[4 * i + 2], d[4 * i + 3]), pack2(d[4 * i + 4], d[4 * i + 5]), pack2(d[4 * i + 6], d[4 * i + 7]));
    }
    wg_wait<0>();
#pragma unroll
    for (int i = 8 * b; i < 64; i++) { float tmp; asm volatile("mov.b32 %0, %1;" : "=f"(tmp) : "f"(d[i])); d[i] = tmp; }
  });
  stsm4t((mi >= 2 && rr + w >= 8) ? pw + 16 * (mi & 1) : paddr + 14 * 256, pack2(d[56], d[57]), pack2(d[58], d[59]), pack2(d[60], d[61]), pack2(d[62], d[63]));
}
__device__ __forceinline__ void conv_fin(uint32_t cv, const uint32_t (&pq)[4], int t, uint32_t D2) {
#pragma unroll
  for (int h = 0; h < 2; h++) {
    const int c = h * 128 + t;
    const uint4 u = lds128(cv + ((c & 1) ? CV_O : CV_E) + CV_PAD + (c >> 1) * 16);
    uint4 v[4];
#pragma unroll
    for (int q = 0; q < 4; q++) {
      v[q] = lds128(pq[q] + 16 * (c ^ ((c >> 3) & 1)));
      if (h == 0 && c < 2 * q) v[q] = make_uint4(0, 0, 0, 0);
    }
    auto f = [&](uint32_t a, uint32_t b, uint32_t cc, uint32_t d, uint32_t uu) { return bfma(__byte_perm(uu, uu, 0x1032), D2, badd(badd(a, b), badd(cc, d))); };
    sts128(cv + CV_K0 + c * 16, make_uint4(f(v[0].x, v[1].x, v[2].x, v[3].x, u.x), f(v[0].y, v[1].y, v[2].y, v[3].y, u.y),
                                           f(v[0].z, v[1].z, v[2].z, v[3].z, u.z), f(v[0].w, v[1].w, v[2].w, v[3].w, u.w)));
  }
}

template <bool SMID> __global__ void __launch_bounds__(384, 1)
fused_kernel(const __grid_constant__ CUtensorMap tmX, const __grid_constant__ CUtensorMap tmWin, const __grid_constant__ CUtensorMap tmW,
             const __grid_constant__ CUtensorMap tmWo, const __grid_constant__ CUtensorMap tmY, const __grid_constant__ CUtensorMap tmOut,
             const __grid_constant__ CUtensorMap tmWin7, const __grid_constant__ CUtensorMap tmWo7,
             const Params p) {
  extern __shared__ __align__(1024) uint8_t smraw[];
  const uint32_t sb = smem_u32(smraw);
  const int tid = threadIdx.x, warp = __shfl_sync(~0u, tid >> 5, 0), lane = tid & 31;
  int m, j;
  {
    int G, jj;
    if (SMID) {
      uint32_t smid; asm("mov.u32 %0, %%smid;" : "=r"(smid));
      if (smid < 64) { G = (smid >> 1) & 7; jj = (smid >> 4) * 2 + (smid & 1); }
      else if (smid < 120) { int t = (smid - 64) >> 1; G = 1 + t % 7; jj = 8 + (t / 7) * 2 + (smid & 1); }
      else if (smid < 124) { G = -1; jj = smid - 120; }
      else { G = 0; jj = 8 + (smid - 124); if (smid > 131) fail(); }
    } else if (blockIdx.x < 4) { G = -1; jj = blockIdx.x; }
    else { G = (blockIdx.x - 4) >> 4; jj = (blockIdx.x - 4) & 15; }
    if (G < 0) {
      const uint32_t tag = *(volatile uint32_t*)&g_epoch + 1;
      const int nb = jj < 3 ? 4 : 2;
      if (tid < nb * 64) st_rlx64(g_cs + jj * 256 + tid, make_uint2(0, 0));
      const uint32_t sbar = sb + OFF_BAR;
      auto load = [&](int k) {
        mbar_expect_tx(sbar + 8 * k, nb * 8192);
        for (int b = 0; b < nb; b++) tma2d(sb + (k % 6) * 32768 + b * 8192, &tmWin, jj * 256 + b * 64, k * 64, sbar + 8 * k);
      };
      if (tid == 0) {
        for (int k = 0; k < 8; k++) mbar_init(sbar + 8 * k, 1);
        asm volatile("fence.mbarrier_init.release.cluster;" ::: "memory");
        fence_async_smem();
        for (int k = 0; k < 6; k++) load(k);
      }
      __syncthreads();
      float acc[8] = {0, 0, 0, 0, 0, 0, 0, 0};
#pragma unroll 1
      for (int k = 0; k < 8; k++) {
        if (warp < 8) {
          mbar_wait(sbar + 8 * k, 0);
#pragma unroll
          for (int i = 0; i < 8; i++) {
            const uint4 v = lds128(sb + (k % 6) * 32768 + (lane >> 3) * 8192 + (warp + 8 * i) * 128 + (((lane & 7) ^ warp) << 4));
            acc[0] += blo(v.x); acc[1] += bhi(v.x); acc[2] += blo(v.y); acc[3] += bhi(v.y);
            acc[4] += blo(v.z); acc[5] += bhi(v.z); acc[6] += blo(v.w); acc[7] += bhi(v.w);
          }
        }
        if (k == 1) { __syncthreads(); if (tid == 0) { load(6); load(7); } }
      }
      float* ps = (float*)(smraw + 196608);
      if (warp < 8) {
#pragma unroll
        for (int e = 0; e < 8; e++) ps[warp * 256 + lane * 8 + e] = acc[e];
      }
      __syncthreads();
      if (tid < nb * 64) {
        float s = 0;
#pragma unroll
        for (int q = 0; q < 8; q++) s += ps[q * 256 + tid];
        st_rlx64(g_cs + jj * 256 + tid, make_uint2(__float_as_uint(s), tag));
      }
      if (tid == 0) STAMP(50);
      if (warp == 0) for (int it = 0; it < 400; it++) { if (ld_rlx(g_cnt + (tag & 1) * 32) >= 112) break; __nanosleep(200); }
      return;
    }
    m = (G >> 1) * 4 + (jj >> 2); j = (G & 1) * 4 + (jj & 3);
  }
  const uint32_t bars = sb + OFF_BAR;
#define BAR(i) (bars + 8 * (i))
  const bool dz2 = j < 7;
  if (lane == 0) {
    auto init_range = [&](auto lo, auto hi) {
      sfor<decltype(lo)::v, decltype(hi)::v>([&](auto ii) {
        constexpr int i = decltype(ii)::v;
        constexpr int cnt = i == B_ZS ? 3 : (i == B_KE || i == B_P1 || (i >= B_WE && i < B_GF) || (i >= B_GE && i < B_CS) || (i >= B_HE && i < B_CVB) || i == B_CVF || i == B_CVF + 1) ? 2 : 1;
        mbar_init(BAR(i), cnt);
      });
    };
    if (warp == 8) {
      sfor<0, NPRO>([&](auto kc) {
        constexpr int k = decltype(kc)::v;
        mbar_init(BAR(B_XF + k), 1); mbar_init(BAR(B_WF + k), 1);
        asm volatile("fence.mbarrier_init.release.cluster;" ::: "memory");
        if (k == 0) STAMP(28);
        mbar_expect_tx(BAR(B_XF + k), 16384); tma2d(sb + OFF_X + k * 16384, &tmX, k * 64, m * 128, BAR(B_XF + k));
        if (dz2) {
          mbar_expect_tx(BAR(B_WF + k), 16384);
          tma2d(sb + wslot(k), &tmWin, FH_ + j * 128, k * 64, BAR(B_WF + k));
          tma2d(sb + wslot(k) + 8192, &tmWin, FH_ + j * 128 + 64, k * 64, BAR(B_WF + k));
        }
      });
      init_range(IC<NPRO>{}, IC<8>{}); init_range(IC<8 + NPRO>{}, IC<14>{});
    }
    else if (warp == 0) init_range(IC<14>{}, IC<20>{});
    else if (warp == 1) init_range(IC<20>{}, IC<26>{});
    else if (warp == 2) init_range(IC<26>{}, IC<32>{});
    else if (warp == 3) init_range(IC<32>{}, IC<38>{});
    else if (warp == 4) init_range(IC<38>{}, IC<44>{});
    else if (warp == 5) init_range(IC<44>{}, IC<50>{});
    else if (warp == 6) init_range(IC<50>{}, IC<55>{});
    else if (warp == 7) init_range(IC<55>{}, IC<60>{});
    else if (warp == 9) init_range(IC<60>{}, IC<65>{});
    else if (warp == 10) init_range(IC<65>{}, IC<70>{});
    else init_range(IC<70>{}, IC<B_NUM>{});
    asm volatile("fence.mbarrier_init.release.cluster;" ::: "memory");
  }
  __syncwarp();
  if (warp == 8) asm volatile("bar.arrive 4, 384;" ::: "memory");
  else { asm volatile("bar.arrive 5, 384;" ::: "memory"); bar_sync(4, 384); }
  if (tid == 0) STAMP(30);

  if (warp >= 8) {
    asm volatile("setmaxnreg.dec.sync.aligned.u32 104;");
    if (warp == 8) {
      if (lane == 0) {
        auto ldx = [&](int k) { mbar_expect_tx(BAR(B_XF + k), 16384); tma2d(sb + OFF_X + k * 16384, &tmX, k * 64, m * 128, BAR(B_XF + k)); };
        auto ldw = [&](int k, uint32_t dst) {
          const int c0 = (k < 8 ? FH_ : 0) + j * 128;
          mbar_expect_tx(BAR(B_WF + k), 16384);
          tma2d(dst, &tmWin, c0, (k & 7) * 64, BAR(B_WF + k));
          tma2d(dst + 8192, &tmWin, c0 + 64, (k & 7) * 64, BAR(B_WF + k));
        };
        if (dz2) {
          for (int k = NPRO; k < 6; k++) { ldx(k); ldw(k, sb + wslot(k)); }
          ldx(6); ldx(7);
        } else {
          for (int k = NPRO; k < 2; k++) ldx(k);
          if (m < 14) {
            mbar_expect_tx(BAR(B_WF), 8 * 8192);
            for (int b = 0; b < 8; b++) tma2d(sb + OFF_WR + b * 8192, &tmWin, FH_ + m * 64, b * 64, BAR(B_WF));
          }
          for (int k = NPRO > 2 ? NPRO : 2; k < 8; k++) ldx(k);
        }
        if (sb & 1023) fail();
        STAMP(31);
      }
      __syncwarp();
      bar_sync(5, 384);
      if (lane == 0) {
        auto ldw = [&](int k, uint32_t dst) {
          const int c0 = (k < 8 ? FH_ : 0) + j * 128;
          mbar_expect_tx(BAR(B_WF + k), 16384);
          tma2d(dst, &tmWin, c0, (k & 7) * 64, BAR(B_WF + k));
          tma2d(dst + 8192, &tmWin, c0 + 64, (k & 7) * 64, BAR(B_WF + k));
        };
        uint32_t slot = sb + wslot(dz2 ? 6 : 8);
        for (int k = dz2 ? 6 : 8; k < 16; k++) {
          mbar_wait(BAR(B_WE + k - 6), 0);
          if (dz2) ldw(k, slot);
          else { mbar_expect_tx(BAR(B_WF + k), 14336); tma3d(slot, &tmWin7, 0, (k & 7) * 64, 0, BAR(B_WF + k)); }
          slot = k == 11 ? sb + OFF_WR : slot + 16384;
        }
        if (m < 8) tma2d_pf(&tmWo, j * 64, m * 112);
        STAMP(32);
      }
      __syncwarp();
      mbar_wait(BAR(B_EP), 0);
      const uint32_t tag = lds32(sb + OFF_EP);
      auto ldA = [&](int k, int s) { mbar_expect_tx(BAR(B_GF + s), G2_STB); tma2d(sb + s * G2_STB, &tmW, k * 64, m * 128, BAR(B_GF + s)); };
      const uint8_t* zsrc = (const uint8_t*)g_z2 + j * 14336;
      auto ldB = [&](int k, int s) { bulk_g2s(sb + s * G2_STB + 16384, zsrc + (size_t)k * ZSLAB, 14336, BAR(B_GF + s)); };
      mbar_wait(BAR(B_ZS), 0);
      if (lane == 0) {
        STAMP(33);
        ldA(0, 0);
      }
      {
        uint32_t it = 0;
        while (ld_rlx(g_cnt + (tag & 1) * 32) < 112) if (++it > (1u << 20)) fail();
        asm volatile("fence.acquire.gpu;" ::: "memory");
        fence_async_glob();
      }
      int s = 0; uint32_t ph = 0;
      if (lane == 0) {
        STAMP(34);
        ldB(0, 0);
        for (int k = 1; k < G2_ST; k++) { ldA(k, k); ldB(k, k); }
        for (int k = G2_ST; k < 35; k++) {
          mbar_wait(BAR(B_GE + s), ph);
          if (k < 32) { ldA(k, s); ldB(k, s); }
          else {
            const int q = k - 32;
            mbar_expect_tx(BAR(B_WOF + q), TILE_B);
            tma2d(sb + OFF_WO + q * TILE_B, &tmWo, j * 64, q * 256, BAR(B_WOF + q));
            tma2d(sb + OFF_WO + q * TILE_B + 14336, &tmWo, j * 64, q * 256 + 128, BAR(B_WOF + q));
          }
          if (++s == G2_ST) { s = 0; ph ^= 1; }
        }
      }
      __syncwarp();
      poll_flags<1>(g_fh + m * 64, 8, tag, lane);
      if (lane == 0) {
        STAMP(35);
        const uint8_t* hsrc = (const uint8_t*)g_h + (size_t)m * 8 * TILE_B;
        auto ldH = [&](int t, uint32_t dst) { mbar_expect_tx(BAR(B_XF + t), TILE_B); bulk_g2s(sb + dst, hsrc + t * TILE_B, TILE_B, BAR(B_XF + t)); };
        ldH(0, hslot(0)); ldH(1, hslot(1));
        mbar_wait(BAR(B_CVA), 0);
        mbar_expect_tx(BAR(B_FX), 16384); tma2d(sb + OFF_XF, &tmX, j * 64, m * 128, BAR(B_FX));
        mbar_wait(BAR(B_WF + 6), dz2); mbar_wait(BAR(B_WF + 7), dz2);
        ldH(2, hslot(2));
        mbar_wait(BAR(B_HE), 0); ldH(3, hslot(3));
        mbar_wait(BAR(B_HE + 1), 0); ldH(4, hslot(4)); ldH(5, hslot(5));
        mbar_wait(BAR(B_CVB), 0);
        mbar_expect_tx(BAR(B_WOF + 3), TILE_B);
        tma2d(sb + OFF_WO6, &tmWo, j * 64, 6 * 128, BAR(B_WOF + 3));
        tma3d(sb + OFF_WO6 + 14336, &tmWo7, j * 64, 0, 0, BAR(B_WOF + 3));
        mbar_wait(BAR(B_HE + 2), 0); ldH(6, hslot(6));
        mbar_wait(BAR(B_HE + 3), 0); ldH(7, hslot(7));
      }
      __syncwarp();
      poll_flags<1>(g_fy + j * 256, 32, tag, lane);
      if (lane == 0) {
        STAMP(36);
        mbar_expect_tx(BAR(B_FY), 16384);
        tma2d(sb + OFF_YF, &tmY, m * 128, j * 64, BAR(B_FY));
        tma2d(sb + OFF_YF + 8192, &tmY, m * 128 + 64, j * 64, BAR(B_FY));
      }
    } else {
      const int hw = warp - 9;
      auto kappa_prep = [&](int part) {
        uint4 v[16];
        const uint8_t* ksrc = (const uint8_t*)p.ssm_k + (size_t)(j * 64 + m * 4 + part * 2) * 4096 + lane * 16;
#pragma unroll
        for (int i = 0; i < 16; i++) v[i] = ldg128(ksrc + i * 512);
        mbar_wait(BAR(B_P1), 0);
#pragma unroll
        for (int ch = 0; ch < 2; ch++) {
          const uint32_t cv = sb + (part ? OFF_CV2 : OFF_CV) + ch * CV_CH;
          uint32_t carry = 0;
#pragma unroll
          for (int i = 0; i < 8; i++) {
            const uint4 x = v[ch * 8 + i];
            uint32_t prev = __shfl_up_sync(~0u, x.w, 1);
            if (lane == 0) prev = carry;
            carry = __shfl_sync(~0u, x.w, 31);
            sts128(cv + CV_K0 + 32 + (i * 32 + lane) * 16, x);
            sts128(cv + CV_K1 + 32 + (i * 32 + lane) * 16,
                   make_uint4(__byte_perm(prev, x.x, 0x5432), __byte_perm(x.x, x.y, 0x5432), __byte_perm(x.y, x.z, 0x5432), __byte_perm(x.z, x.w, 0x5432)));
          }
          const uint4 z = make_uint4(0, 0, 0, 0);
          if (lane < 2) sts128(cv + CV_K0 + lane * 16, z);
          else if (lane < 4) sts128(cv + CV_K1 + (lane - 2) * 16, z);
        }
        __syncwarp();
        if (lane == 0) mbar_arrive(BAR(B_CVF + part));
      };
      auto u_load = [&](int part) {
        uint4 v[16];
        const uint4* usrc = g_kv + (size_t)(j * 64 + m * 4 + part * 2) * 256 + lane;
#pragma unroll
        for (int i = 0; i < 16; i++) v[i] = __ldcg(usrc + i * 32);
        const uint32_t cb = sb + (part ? OFF_CV2 : OFF_CV);
#pragma unroll
        for (int i = 0; i < 16; i++) sts128(cb + (i >> 3) * CV_CH + ((i & 4) ? CV_O : CV_E) + CV_PAD + ((i & 3) * 32 + lane) * 16, v[i]);
        if (lane < 24) {
          const uint32_t a = cb + (lane < 12 ? CV_E + lane * 16 : CV_O + (lane - 12) * 16);
          sts128(a, make_uint4(0, 0, 0, 0)); sts128(a + CV_CH, make_uint4(0, 0, 0, 0));
        }
        fence_async_smem();
        __syncwarp();
        if (lane == 0) mbar_arrive(BAR(B_CVF + part));
      };
      uint32_t tag = 0;
      if (hw == 0) {
        tag = *(volatile uint32_t*)&g_epoch + 1;
        if (lane == 0) { asm volatile("st.shared.b32 [%0], %1;" ::"r"(sb + OFF_EP), "r"(tag) : "memory"); mbar_arrive(BAR(B_EP)); }
        if (lane == 0) {
          if (m == 0 && j == 0) st_flag(g_cnt + ((tag + 1) & 1) * 32, 0);
          st_flag(g_fy + (j * 32 + m * 2) * 8, 0); st_flag(g_fy + (j * 32 + m * 2 + 1) * 8, 0);
          st_flag(g_fh + (m * 8 + j) * 8, 0);
        }
        if (dz2) {
          uint4 v0, v1; uint32_t it = 0;
          do {
            v0 = ld_rlx128(g_cz + j * 64 + lane); v1 = ld_rlx128(g_cz + j * 64 + 32 + lane);
            if (++it > (1u << 20)) fail();
          } while (v0.z != tag || v1.z != tag);
          asm volatile("st.shared.v2.b32 [%0], {%1, %2};" ::"r"(sb + OFF_CS + lane * 8), "r"(v0.x), "r"(v0.y) : "memory");
          asm volatile("st.shared.v2.b32 [%0], {%1, %2};" ::"r"(sb + OFF_CS + 256 + lane * 8), "r"(v1.x), "r"(v1.y) : "memory");
          __syncwarp();
          if (lane == 0) { mbar_arrive(BAR(B_CZ)); STAMP(39); }
        }
        {
          uint2 v[4]; uint32_t it = 0; bool ok;
          do {
            ok = true;
#pragma unroll
            for (int i = 0; i < 4; i++) if (lane + 32 * i < 112) { const int q = lane + 32 * i; v[i] = ld_rlx64(g_cs + (dz2 ? j * 128 + q : (q >> 4) * 128 + 112 + (q & 15))); ok &= (v[i].y == tag); }
            if (++it > (1u << 20)) fail();
          } while (!ok);
#pragma unroll
          for (int i = 0; i < 4; i++) if (lane + 32 * i < 112) asm volatile("st.shared.b32 [%0], %1;" ::"r"(sb + OFF_CS + 512 + (lane + 32 * i) * 4), "r"(v[i].x) : "memory");
          __syncwarp();
          if (lane == 0) { mbar_arrive(BAR(B_CS)); STAMP(41); }
        }
        if (lane == 0) {
          uint8_t* hdst = (uint8_t*)g_h + (size_t)(m * 8 + j) * TILE_B;
          uint8_t* ydst = (uint8_t*)g_y + (size_t)(j * 64 + m * 4) * 4096;
          if (dz2) {
            for (int wg = 0; wg < 2; wg++) {
              uint8_t* zdst = (uint8_t*)g_z2 + (size_t)(m * 2 + wg) * ZSLAB;
              mbar_wait(BAR(B_WF + wg), 1);
              bulk_s2g(zdst + j * 14336, sb + OFF_X + wg * 8192, 8192);
              bulk_s2g(zdst + j * 14336 + 8192, sb + OFF_X + 16384 + wg * 8192, 6144);
              bulk_s2g(zdst + 7 * 14336 + j * 2048, sb + OFF_X + 16384 + wg * 8192 + 6144, 2048);
            }
            bulk_commit(); bulk_wait<0>();
            fence_gpu();
            asm volatile("red.relaxed.gpu.global.add.u32 [%0], 1;" ::"l"(g_cnt + (tag & 1) * 32) : "memory");
          }
          mbar_arrive(BAR(B_ZS));
          STAMP(46);
          for (int wg = 0; wg < 2; wg++) {
            mbar_wait(BAR(B_WF + 4 + wg), dz2);
            bulk_s2g(hdst + wg * 14336, sb + wg * 8192, 7168);
            bulk_s2g(hdst + wg * 14336 + 7168, sb + G2_STB + wg * 8192, 7168);
          }
          bulk_commit(); bulk_wait<0>();
          fence_gpu();
          st_flag(g_fh + (m * 8 + j) * 8, tag);
          STAMP(47);
          for (int wg = 0; wg < 2; wg++) { mbar_wait(BAR(B_WF + 2 + wg), dz2); bulk_s2g(ydst + wg * 4096, sb + OFF_CV + wg * CV_CH + CV_K0, 4096); }
          bulk_commit(); bulk_wait<0>();
          mbar_arrive(BAR(B_CVA));
          fence_gpu();
          st_flag(g_fy + (j * 32 + m * 2) * 8, tag);
          for (int wg = 0; wg < 2; wg++) { mbar_wait(BAR(B_WF + 6 + wg), dz2); bulk_s2g(ydst + (2 + wg) * 4096, sb + OFF_CV2 + wg * CV_CH + CV_K0, 4096); }
          bulk_commit(); bulk_wait<0>();
          mbar_arrive(BAR(B_CVB));
          fence_gpu();
          st_flag(g_fy + (j * 32 + m * 2 + 1) * 8, tag);
          STAMP(48);
        }
      } else {
        if (hw == 1 && lane == 0) st_flag(g_fk + (j * 16 + m) * 8, 0);
        auto pf_rows = [&](const void* base) {
          const uint8_t* q = (const uint8_t*)base + (hw - 1) * 8192 + lane * 128;
          asm volatile("prefetch.global.L2 [%0];" ::"l"(q));
          asm volatile("prefetch.global.L2 [%0];" ::"l"(q + 4096));
        };
        mbar_wait(BAR(B_XF + 3), 0);
        if (dz2) asm volatile("prefetch.global.L2 [%0];" ::"l"((const uint8_t*)p.w_in + (size_t)(m * 32 + lane) * (F_ * 2) + j * 256 + (hw - 1) * 128));
        mbar_wait(BAR(B_XF + 7), 0);
        if (lane == 0 && hw == 1) STAMP(51);
        pf_rows(p.k + (size_t)(m * 128 + j * 16) * D_);
        mbar_wait(BAR(B_WF + 9), 0);
        pf_rows(p.v + (size_t)(m * 128 + j * 16) * D_);
        mbar_wait(BAR(B_WF + 12), 0);
        kappa_prep(hw - 1);
        if (lane == 0) STAMP(41 + hw);
        {
          const int d0 = j * 64 + (lane >> 1) * 4;
          uint32_t wt[2][4];
#pragma unroll
          for (int q = 0; q < 2; q++) {
            const uint4 tp = ldg128(p.shift + (d0 + 2 * q) * 4);
            wt[q][0] = __byte_perm(tp.x, tp.z, 0x5410); wt[q][1] = __byte_perm(tp.x, tp.z, 0x7632);
            wt[q][2] = __byte_perm(tp.y, tp.w, 0x5410); wt[q][3] = __byte_perm(tp.y, tp.w, 0x7632);
          }
          mbar_wait(BAR(B_GF + KV_ST), 0);
#pragma unroll 1
          for (int bt = 0; bt < 2; bt++) {
            const int blk = (hw - 1) * 4 + bt * 2 + (lane & 1), s0 = m * 128 + blk * 16;
            uint2 kk[19], vv[16];
#pragma unroll
            for (int i = 0; i < 19; i++) kk[i] = (i >= 3 || s0 > 0) ? ldg64(p.k + (size_t)(s0 - 3 + i) * D_ + d0) : make_uint2(0, 0);
#pragma unroll
            for (int i = 0; i < 16; i++) vv[i] = ldg64(p.v + (size_t)(s0 + i) * D_ + d0);
            uint4* dst = g_kv + (size_t)d0 * 256 + m * 8 + blk;
#pragma unroll
            for (int q = 0; q < 2; q++) {
#pragma unroll
              for (int cc = 0; cc < 2; cc++) {
                uint32_t u[8];
#pragma unroll
                for (int e = 0; e < 8; e++) {
                  const int i = cc * 8 + e;
                  auto c_ = [&](const uint2& a) { return q ? a.y : a.x; };
                  u[e] = bmul(bfma(c_(kk[i + 3]), wt[q][0], bfma(c_(kk[i + 2]), wt[q][1], bfma(c_(kk[i + 1]), wt[q][2], bmul(c_(kk[i]), wt[q][3])))), c_(vv[i]));
                }
                dst[q * 512 + cc * 128] = make_uint4(__byte_perm(u[1], u[0], 0x5410), __byte_perm(u[3], u[2], 0x5410), __byte_perm(u[5], u[4], 0x5410), __byte_perm(u[7], u[6], 0x5410));
                dst[q * 512 + cc * 128 + 256] = make_uint4(__byte_perm(u[1], u[0], 0x7632), __byte_perm(u[3], u[2], 0x7632), __byte_perm(u[5], u[4], 0x7632), __byte_perm(u[7], u[6], 0x7632));
              }
            }
            if (lane == 0 && hw == 1) STAMP(52 + bt);
          }
          __syncwarp();
          if (lane == 0) mbar_arrive(BAR(B_KE));
        }
        if (hw == 1) {
          mbar_wait(BAR(B_EP), 0);
          tag = lds32(sb + OFF_EP);
          mbar_wait(BAR(B_KE), 0);
          if (lane == 0) { fence_gpu(); st_flag(g_fk + (j * 16 + m) * 8, tag); STAMP(44); }
          __syncwarp();
          poll_flags<1>(g_fk + j * 128, 16, tag, lane);
          u_load(0);
          u_load(1);
          if (lane == 0) STAMP(49);
        }
      }
    }
  } else {
    asm volatile("setmaxnreg.inc.sync.aligned.u32 200;");
    const int wg = warp >> 2, w = warp & 3, g = lane >> 2, tq = lane & 3, t = tid & 127;
    const bool el = (t == 0);
    const int row0 = wg * 64 + w * 16 + g;
    const int lr = wg * 64 + w * 16 + (lane & 7) + ((lane >> 3) & 1) * 8;
    const uint32_t lrow = lr * 128, lsw = lane & 7, lhi = lane >> 4;

    float z2[64], z1[56];
    constexpr uint32_t H128 = dhi(1024, 1);
    const uint32_t dX = dlo(sb + OFF_X + wg * 8192, 16), dW = dlo(sb, 8192);
    const uint32_t dW1 = dz2 ? dW : dlo(sb, 2048), hW1 = dz2 ? H128 : dhi(256, 3), stepW1 = dz2 ? 128 : 32;
    auto z1_issue = [&](auto kc) {
      constexpr int k = decltype(kc)::v;
      mbar_wait(BAR(B_WF + k), 0);
      wg_fence();
#pragma unroll
      for (int kk = 0; kk < 4; kk++) wgmma_ss_n112(z1, dX + (k & 7) * 1024 + kk * 2, H128, dW1 + wslot(k) / 16 + kk * stepW1, hW1);
      wg_commit();
      mbar_wait(BAR(B_WF + k), 0);
    };
    if (!dz2) {
      constexpr uint32_t ONE2 = 0x3F803F80u;
      uint4* czp = g_cz + m * 32 + lane;
      if (warp == 0 && m < 14) st_rlx128(czp, make_uint4(0, 0, 0, 0));
      if (tq < 2) st_rlx128(g_xs + m * 128 + row0 + tq * 8, make_uint4(0, 0, 0, 0));
      mbar_wait(BAR(B_EP), 0);
      const uint32_t tg = lds32(sb + OFF_EP);
      float d1[4][4], d3[4][4];
#pragma unroll
      for (int i = 0; i < 4; i++) { d1[i][0] = d1[i][1] = d1[i][2] = d1[i][3] = 0.f; d3[i][0] = d3[i][1] = d3[i][2] = d3[i][3] = 0.f; }
      uint32_t xa[4];
#pragma unroll
      for (int kk = 0; kk < 4; kk++) xa[kk] = sb + OFF_X + lrow + (((2 * kk + lhi) ^ lsw) << 4);
      auto xgrp = [&](int k0) {
        mbar_wait(BAR(B_XF + k0), 0); mbar_wait(BAR(B_XF + k0 + 1), 0);
        if (tid == 0) STAMP(20 + k0);
        uint32_t r[8][4];
#pragma unroll
        for (int i = 0; i < 8; i++) ldsm4(xa[i & 3] + (k0 + (i >> 2)) * 16384, r[i]);
#pragma unroll
        for (int i = 0; i < 8; i++) {
          mma16816(d1[i & 3], bmul(r[i][0], r[i][0]), bmul(r[i][1], r[i][1]), bmul(r[i][2], r[i][2]), bmul(r[i][3], r[i][3]), ONE2, ONE2);
          mma16816(d3[i & 3], r[i][0], r[i][1], r[i][2], r[i][3], ONE2, ONE2);
        }
      };
      xgrp(0);
      if (m < 14) {
        mbar_wait(BAR(B_WF), 0);
        float cs[8][4];
#pragma unroll
        for (int i = 0; i < 8; i++) cs[i][0] = cs[i][1] = cs[i][2] = cs[i][3] = 0.f;
        const uint32_t ba = sb + OFF_WR + warp * 8192 + (lane & 15) * 128;
#pragma unroll
        for (int kk = 0; kk < 4; kk++) {
#pragma unroll
          for (int i = 0; i < 8; i += 2) {
            uint32_t r[4];
            ldsm4t(ba + kk * 2048 + (((i + lhi) ^ lsw) << 4), r);
            mma16816(cs[i], ONE2, ONE2, ONE2, ONE2, r[0], r[1]);
            mma16816(cs[i + 1], ONE2, ONE2, ONE2, ONE2, r[2], r[3]);
          }
        }
        float a = cs[0][0], b = cs[0][1];
#pragma unroll
        for (int i = 1; i < 8; i++) if (g == i) { a = cs[i][0]; b = cs[i][1]; }
        asm volatile("st.shared.v2.f32 [%0], {%1, %2};" ::"r"(sb + 196608 + warp * 256 + lane * 8), "f"(a), "f"(b) : "memory");
      }
      bar_sync(3, 256);
      if (warp == 0 && m < 14) {
        float a = 0, b = 0;
#pragma unroll
        for (int q = 0; q < 8; q++) { const float2 v = lds64f(sb + 196608 + q * 256 + lane * 8); a += v.x; b += v.y; }
        st_rlx128(czp, make_uint4(__float_as_uint(a), __float_as_uint(b), tg, 0));
      }
      if (el) for (int k = 0; k < 7; k++) if (k != 4 || wg) mbar_arrive(BAR(B_WE + k));
      if (tid == 0) mbar_arrive(BAR(B_WE + 4));
      if (tid == 0) STAMP(40);
      xgrp(2); xgrp(4); xgrp(6);
      const float qa = d1[0][0] + d1[1][0] + d1[2][0] + d1[3][0], qb = d1[0][2] + d1[1][2] + d1[2][2] + d1[3][2];
      const float mu = (tq ? d3[0][2] + d3[1][2] + d3[2][2] + d3[3][2] : d3[0][0] + d3[1][0] + d3[2][0] + d3[3][0]) * (1.f / 512);
      const float ve = fmaxf((tq ? qb : qa) * (1.f / 512) - mu * mu, 0.f) + 1e-5f, rs = rsqrtf(ve);
      if (tq < 2) st_rlx128(g_xs + m * 128 + row0 + tq * 8, make_uint4(__float_as_uint(mu), __float_as_uint(rs), tg, __float_as_uint(4e-5f * ve)));
      if (tid == 0) STAMP(37);
    }
    zero_acc(z2); zero_acc(z1);
    if (tid == 0) STAMP(1);
    uint4 xs0, xs1;
    sfor<0, 8>([&](auto kc) {
      constexpr int k = decltype(kc)::v;
      mbar_wait(BAR(B_XF + k), 0);
      if (k == 0 && tid == 0) STAMP(29);
      if (dz2) {
        mbar_wait(BAR(B_WF + k), 0);
        wg_fence();
#pragma unroll
        for (int kk = 0; kk < 4; kk++) wgmma_ss_n128(z2, dX + k * 1024 + kk * 2, H128, dW + wslot(k) / 16 + kk * 128, H128);
        wg_commit();
      }
      if (tid == 0 && dz2) STAMP(20 + k);
      if constexpr (k == 0) { if (dz2 && tq < 2) st_rlx128(g_st + (m * 7 + j) * 128 + row0 + tq * 8, make_uint4(0, 0, 0, 0)); }
      if constexpr (k == XS_K) { xs0 = ld_rlx128(g_xs + m * 128 + row0); xs1 = ld_rlx128(g_xs + m * 128 + row0 + 8); }
      wg_wait<1>();
      if (k > 0 && dz2 && el) mbar_arrive(BAR(B_WE + k - 1));
    });
    z1_issue(IC<8>{});
    mbar_wait(BAR(B_EP), 0);
    const uint32_t tag = lds32(sb + OFF_EP);
    float mu0, rs0, mu1, rs1, ep0, ep1;
    {
      uint4 v0 = xs0, v1 = xs1; uint32_t it = 0;
      while (v0.z != tag || v1.z != tag) {
        v0 = ld_rlx128(g_xs + m * 128 + row0); v1 = ld_rlx128(g_xs + m * 128 + row0 + 8);
        if (++it > (1u << 20)) fail();
      }
      __syncwarp();
      if (tid == 0) STAMP(38);
      mu0 = __uint_as_float(v0.x); rs0 = __uint_as_float(v0.y); mu1 = __uint_as_float(v1.x); rs1 = __uint_as_float(v1.y);
      ep0 = __uint_as_float(v0.w); ep1 = __uint_as_float(v1.w);
    }
    const RowC c0 = {-mu0, rs0 * 0.7978845608f, rs0 * rs0 * rs0 * 0.0356774081f};
    const RowC c1 = {-mu1, rs1 * 0.7978845608f, rs1 * rs1 * rs1 * 0.0356774081f};
    wg_wait<1>();
    if (el) mbar_arrive(BAR(B_WE + 7));
    if (tid == 0) STAMP(2);
    auto pump = [&](auto kc) {
      constexpr int k = decltype(kc)::v;
      wg_wait<1>();
      if (k - 2 < 10 && el) mbar_arrive(BAR(B_WE + k - 2));
      z1_issue(kc);
    };
    float a0 = 0, a1 = 0, e0 = 0, e1 = 0;
    auto gelu_seg = [&](auto& z, uint32_t csa, auto lo, auto hi, auto st) {
      sfor<decltype(lo)::v, decltype(hi)::v>([&](auto ii) {
        constexpr int i = decltype(ii)::v;
        const float2 cs = lds64f(csa + i * 32 + tq * 8);
        z[4 * i] = gelu_f(z[4 * i], cs.x, c0); z[4 * i + 1] = gelu_f(z[4 * i + 1], cs.y, c0);
        z[4 * i + 2] = gelu_f(z[4 * i + 2], cs.x, c1); z[4 * i + 3] = gelu_f(z[4 * i + 3], cs.y, c1);
        if constexpr (decltype(st)::v) {
          a0 += z[4 * i]; a0 += z[4 * i + 1]; a1 += z[4 * i + 2]; a1 += z[4 * i + 3];
          e0 = fmaf(z[4 * i], z[4 * i], e0); e0 = fmaf(z[4 * i + 1], z[4 * i + 1], e0);
          e1 = fmaf(z[4 * i + 2], z[4 * i + 2], e1); e1 = fmaf(z[4 * i + 3], z[4 * i + 3], e1);
        }
      });
    };
    auto staged = [&](int ev) { fence_async_smem(); bar_sync(1 + wg, 128); if (el) mbar_arrive(BAR(B_WF + ev * 2 + wg)); };
    if (dz2) {
      mbar_wait(BAR(B_CZ), 0);
      gelu_seg(z2, sb + OFF_CS, IC<0>{}, IC<16>{}, IC<1>{});
      a0 = qsum(a0); a1 = qsum(a1); e0 = qsum(e0); e1 = qsum(e1);
      e0 = fmaxf(e0 - a0 * a0 * (1.f / 128), 0.f); e1 = fmaxf(e1 - a1 * a1 * (1.f / 128), 0.f);
      if (tq < 2) st_rlx128(g_st + (m * 7 + j) * 128 + row0 + tq * 8, make_uint4(__float_as_uint(tq ? a1 : a0), __float_as_uint(tq ? e1 : e0), tag, 0));
    }
    if (tid == 0) STAMP(3);
    z1_issue(IC<9>{});
    pump(IC<10>{});
    if (tid == 0) STAMP(7);
    float r20 = 0, r21 = 0, nm0 = 0, nm1 = 0;
    if (dz2) {
      const uint4* sp = g_st + (m * 7 + 2 * tq) * 128 + row0;
      const int o2 = tq < 3 ? 128 : 0;
      uint4 v0, v1, v2, v3; uint32_t it = 0;
      do {
        v0 = ld_rlx128(sp); v1 = ld_rlx128(sp + o2); v2 = ld_rlx128(sp + 8); v3 = ld_rlx128(sp + o2 + 8);
        if (++it > (1u << 20)) fail();
      } while (v0.z != tag || v1.z != tag || v2.z != tag || v3.z != tag);
      __syncwarp();
      if (tid == 0) STAMP(4);
      const float wt = tq < 3 ? 1.f : 0.f;
      const float me0 = qsum(fmaf(wt, __uint_as_float(v1.x), __uint_as_float(v0.x))) * (1.f / 896);
      const float me1 = qsum(fmaf(wt, __uint_as_float(v3.x), __uint_as_float(v2.x))) * (1.f / 896);
      float x;
      x = __uint_as_float(v0.x) * (1.f / 128) - me0; e0 = fmaf(128.f * x, x, __uint_as_float(v0.y));
      x = __uint_as_float(v1.x) * (1.f / 128) - me0; e0 = fmaf(wt, fmaf(128.f * x, x, __uint_as_float(v1.y)), e0);
      x = __uint_as_float(v2.x) * (1.f / 128) - me1; e1 = fmaf(128.f * x, x, __uint_as_float(v2.y));
      x = __uint_as_float(v3.x) * (1.f / 128) - me1; e1 = fmaf(wt, fmaf(128.f * x, x, __uint_as_float(v3.y)), e1);
      r20 = rsq(fmaf(qsum(e0), 1.f / 896, ep0)); r21 = rsq(fmaf(qsum(e1), 1.f / 896, ep1));
      nm0 = -me0 * r20; nm1 = -me1 * r21;
    }
    wg_wait<1>();
    if (el) mbar_arrive(BAR(B_WE + 9));
    if (dz2) {
      const uint32_t za = sb + OFF_X + wg * 8192 + (lane >> 4) * 1024 + (2 * w + ((lane >> 3) & 1)) * 128 + (lane & 7) * 16;
#pragma unroll
      for (int i = 0; i < 16; i += 2)
        stsm4(za + (i >> 3) * 16384 + (i & 7) * 1024,
              pack2(fmaf(z2[4 * i], r20, nm0), fmaf(z2[4 * i + 1], r20, nm0)), pack2(fmaf(z2[4 * i + 2], r21, nm1), fmaf(z2[4 * i + 3], r21, nm1)),
              pack2(fmaf(z2[4 * i + 4], r20, nm0), fmaf(z2[4 * i + 5], r20, nm0)), pack2(fmaf(z2[4 * i + 6], r21, nm1), fmaf(z2[4 * i + 7], r21, nm1)));
      staged(0);
    }
    if (tid == 0) STAMP(5);
    z1_issue(IC<11>{});
    pump(IC<12>{});
    pump(IC<13>{});
    pump(IC<14>{});
    pump(IC<15>{});
    wg_wait<0>();
    if (el) { mbar_arrive(BAR(B_ZS)); mbar_arrive(BAR(B_P1)); }
    if (tid == 0) STAMP(6);
    uint32_t z1p[28];
    mbar_wait(BAR(B_CS), 0);
    gelu_seg(z1, sb + OFF_CS + 512, IC<0>{}, IC<14>{}, IC<0>{});
#pragma unroll
    for (int i = 0; i < 28; i++) z1p[i] = pack2(z1[2 * i], z1[2 * i + 1]);
    if (tid == 0) STAMP(8);
    float acc[56];
    zero_acc(acc);
    uint32_t rb0, rb1, rdA, rdB;
    {
      const uint32_t dA = dlo(sb + wg * 8192, 16), dB = dlo(sb + 16384, 128);
      auto issue = [&](auto sc, uint32_t ph) {
        constexpr int s = decltype(sc)::v;
        mbar_wait(BAR(B_GF + s), ph);
        wg_fence();
#pragma unroll
        for (int kk = 0; kk < 4; kk++) wgmma_ss_n112(acc, dA + s * (G2_STB / 16) + kk * 2, H128, dB + s * (G2_STB / 16) + kk * 16, dhi(1024, 0));
        wg_commit();
      };
      auto step = [&](auto sc, uint32_t ph) {
        constexpr int s = decltype(sc)::v;
        issue(sc, ph);
        wg_wait<1>();
        if (el) mbar_arrive(BAR(B_GE + (s + G2_ST - 1) % G2_ST));
      };
      rb0 = ldg16(p.b_sp + m * 128 + row0); rb1 = ldg16(p.b_sp + m * 128 + row0 + 8);
      rdA = ldg16(p.ssm_D + j * 64 + m * 4 + wg); rdB = ldg16(p.ssm_D + j * 64 + m * 4 + 2 + wg);
      issue(IC<0>{}, 0);
      if (tid == 0) STAMP(11);
      step(IC<1>{}, 0);
      uint32_t ph = 0;
#pragma unroll 1
      for (int i = 0; i < 6; i++) {
        step(IC<2>{}, ph); step(IC<3>{}, ph); step(IC<4>{}, ph);
        ph ^= 1;
        step(IC<0>{}, ph); step(IC<1>{}, ph);
      }
      wg_wait<0>();
    }
    if (tid == 0) STAMP(12);
    const uint32_t stg = sb + wg * 8192 + (w & 1) * 3584 + ((lane >> 3) & 1) * 1792 + (lane >> 4) * 128 + (lane & 7) * 16;
    const float h0 = 0.5f * rs0, h1 = 0.5f * rs1, hb0 = h0 * blo(rb0), hb1 = h1 * blo(rb1);
#pragma unroll
    for (int i = 0; i < 14; i += 2)
      stsm4(stg + (w >> 1) * G2_STB + i * 128,
            pack2(blo(z1p[2 * i]) * fmaf(acc[4 * i], h0, hb0), bhi(z1p[2 * i]) * fmaf(acc[4 * i + 1], h0, hb0)),
            pack2(blo(z1p[2 * i + 1]) * fmaf(acc[4 * i + 2], h1, hb1), bhi(z1p[2 * i + 1]) * fmaf(acc[4 * i + 3], h1, hb1)),
            pack2(blo(z1p[2 * i + 2]) * fmaf(acc[4 * i + 4], h0, hb0), bhi(z1p[2 * i + 2]) * fmaf(acc[4 * i + 5], h0, hb0)),
            pack2(blo(z1p[2 * i + 3]) * fmaf(acc[4 * i + 6], h1, hb1), bhi(z1p[2 * i + 3]) * fmaf(acc[4 * i + 7], h1, hb1)));
    staged(2);
    if (tid == 0) STAMP(13);
    bar_sync(3, 256);
    if (CONV_SKEW && wg) { const long long t0 = clock64(); while (clock64() - t0 < CONV_SKEW); }
    {
      const uint32_t pb = sb + OFF_P + wg * 12288, p3 = sb + (wg ? OFF_P31 : OFF_P30);
      const uint32_t pq[4] = {pb, pb + 4096, pb + 8192, p3};
      const uint32_t pw = w == 3 ? p3 : pb + w * 4096;
#pragma unroll 1
      for (int r = 0; r < 2; r++) {
        const uint32_t cv = sb + (r ? OFF_CV2 : OFF_CV) + wg * CV_CH;
        mbar_wait(BAR(B_CVF + r), 0);
        conv_mma(cv, pw, w, lane);
        if (tid == 0) STAMP(r ? 14 : 9);
        bar_sync(1 + wg, 128);
        conv_fin(cv, pq, t, (r ? rdB : rdA) * 0x10001u);
        staged(1 + 2 * r);
        if (tid == 0 && r == 0) STAMP(10);
      }
    }
    if (tid == 0) STAMP(15);
    float o[32];
    zero_acc(o);
    {
      const uint32_t dA = dlo(sb + wg * 14336, 128), dB = dlo(sb, 8192);
      sfor<0, 8>([&](auto tc) {
        constexpr int tt = decltype(tc)::v;
        if (!(tt & 1)) mbar_wait(BAR(B_WOF + (tt >> 1)), 0);
        mbar_wait(BAR(B_XF + tt), 1);
        if (tt == 0 && tid == 0) STAMP(16);
        wg_fence();
#pragma unroll
        for (int kk = 0; kk < 7; kk++)
          wgmma_ss_n64(o, dA + hslot(tt) / 16 + kk * 16, dhi(1792, 0), dB + (tt < 6 ? OFF_WO + tt * 14336 : OFF_WO6 + (tt - 6) * 14336) / 16 + kk * 128, H128);
        wg_commit();
        wg_wait<1>();
        if (tt > 0 && tt <= 4 && el) mbar_arrive(BAR(B_HE + tt - 1));
      });
      wg_wait<0>();
    }
    if (tid == 0) STAMP(17);
    mbar_wait(BAR(B_FX), 0);
    mbar_wait(BAR(B_FY), 0);
    if (tid == 0) STAMP(18);
    {
      const uint32_t ybase = sb + OFF_YF + wg * 8192 + ((lane & 7) + (lane >> 4) * 8) * 128 + (((2 * w + ((lane >> 3) & 1)) ^ lsw) << 4);
#pragma unroll
      for (int c = 0; c < 8; c += 2) {
        uint32_t x[4], y[4], r[4];
        const uint32_t xa = sb + OFF_XF + lrow + (((c + lhi) ^ lsw) << 4);
        ldsm4(xa, x);
        ldsm4t(ybase + c * 1024, y);
#pragma unroll
        for (int e = 0; e < 4; e++) {
          const float mu = (e & 1) ? mu1 : mu0, rs = (e & 1) ? rs1 : rs0;
          const float xl = blo(x[e]), xh = bhi(x[e]);
          r[e] = pack2(fmaf((xl - mu) * rs, blo(y[e]), xl + o[4 * c + 2 * e]), fmaf((xh - mu) * rs, bhi(y[e]), xh + o[4 * c + 2 * e + 1]));
        }
        stsm4(xa, r[0], r[1], r[2], r[3]);
      }
      fence_async_smem();
      bar_sync(1 + wg, 128);
      if (el) {
        tma2d_st(&tmOut, j * 64, m * 128 + wg * 64, sb + OFF_XF + wg * 8192);
        asm volatile("cp.async.bulk.commit_group;" ::: "memory");
        if (m == 0 && j == 0 && wg == 0) *(volatile uint32_t*)&g_epoch = tag;
        asm volatile("cp.async.bulk.wait_group.read 0;" ::: "memory");
      }
    }
    if (tid == 0) STAMP(19);
  }
}

typedef CUresult (*EncFn)(CUtensorMap*, CUtensorMapDataType, cuuint32_t, void*, const cuuint64_t*, const cuuint64_t*, const cuuint32_t*,
                          const cuuint32_t*, CUtensorMapInterleave, CUtensorMapSwizzle, CUtensorMapL2promotion, CUtensorMapFloatOOBfill);

void enc3d(EncFn f, CUtensorMap* m, const void* ptr, uint64_t d0, uint64_t d1, uint64_t d2, uint64_t s1, uint64_t s2, uint32_t b0, uint32_t b1,
           uint32_t b2, CUtensorMapSwizzle swz) {
  cuuint64_t dims[3] = {d0, d1, d2}, strides[2] = {s1, s2};
  cuuint32_t box[3] = {b0, b1, b2}, es[3] = {1, 1, 1};
  f(m, CU_TENSOR_MAP_DATA_TYPE_BFLOAT16, 3, const_cast<void*>(ptr), dims, strides, box, es, CU_TENSOR_MAP_INTERLEAVE_NONE, swz,
    CU_TENSOR_MAP_L2_PROMOTION_L2_128B, CU_TENSOR_MAP_FLOAT_OOB_FILL_NONE);
}
void enc2d(EncFn f, CUtensorMap* m, const void* ptr, uint64_t cols, uint64_t rows, uint32_t bc, uint32_t br, CUtensorMapSwizzle swz = CU_TENSOR_MAP_SWIZZLE_128B) {
  cuuint64_t dims[2] = {cols, rows}, strides[1] = {cols * 2};
  cuuint32_t box[2] = {bc, br}, es[2] = {1, 1};
  f(m, CU_TENSOR_MAP_DATA_TYPE_BFLOAT16, 2, const_cast<void*>(ptr), dims, strides, box, es, CU_TENSOR_MAP_INTERLEAVE_NONE,
    swz, CU_TENSOR_MAP_L2_PROMOTION_L2_256B, CU_TENSOR_MAP_FLOAT_OOB_FILL_NONE);
}

}

extern "C" void kernel_launch(void* const* d_in, const int* in_sizes, int n_in, void* d_out, int out_size) {
  (void)in_sizes; (void)n_in; (void)out_size;
  static EncFn enc = nullptr;
  static int nsm = 0;
  static void* yptr = nullptr;
  if (!enc) {
    void* f = nullptr;
    cudaDriverEntryPointQueryResult q;
    cudaGetDriverEntryPoint("cuTensorMapEncodeTiled", &f, cudaEnableDefault, &q);
    enc = (EncFn)f;
    int dev = 0;
    cudaGetDevice(&dev);
    cudaDeviceGetAttribute(&nsm, cudaDevAttrMultiProcessorCount, dev);
    cudaFuncSetAttribute(fused_kernel<true>, cudaFuncAttributeMaxDynamicSharedMemorySize, SM_TOTAL);
    cudaFuncSetAttribute(fused_kernel<false>, cudaFuncAttributeMaxDynamicSharedMemorySize, SM_TOTAL);
    cudaGetSymbolAddress(&yptr, g_y);
  }
  CUtensorMap tmX, tmWin, tmW, tmWo, tmY, tmOut, tmWin7, tmWo7;
  enc2d(enc, &tmX, d_in[0], D_, S_, 64, 128);
  enc2d(enc, &tmWin, d_in[7], F_, D_, 64, 64);
  enc2d(enc, &tmW, d_in[8], S_, S_, 64, 128);
  enc2d(enc, &tmWo, d_in[10], D_, FH_, 64, 112);
  enc3d(enc, &tmWin7, (const uint8_t*)d_in[7] + 224, 16, D_, 7, F_ * 2, 256, 16, 64, 7, CU_TENSOR_MAP_SWIZZLE_32B);
  enc3d(enc, &tmWo7, (const uint8_t*)d_in[10] + 112 * 1024, D_, 16, 7, 1024, 128 * 1024, 64, 16, 7, CU_TENSOR_MAP_SWIZZLE_128B);
  enc2d(enc, &tmY, yptr, S_, D_, 64, 64);
  enc2d(enc, &tmOut, d_out, D_, S_, 64, 64);
  Params p;
  p.x = (const __nv_bfloat16*)d_in[0];
  p.k = (const __nv_bfloat16*)d_in[1]; p.v = (const __nv_bfloat16*)d_in[2]; p.shift = (const __nv_bfloat16*)d_in[3];
  p.ssm_k = (const __nv_bfloat16*)d_in[4]; p.ssm_D = (const __nv_bfloat16*)d_in[5]; p.w_in = (const __nv_bfloat16*)d_in[7];
  p.b_sp = (const __nv_bfloat16*)d_in[9]; p.w_sp = (const __nv_bfloat16*)d_in[8];
  if (nsm == 132) fused_kernel<true><<<132, 384, SM_TOTAL, cudaStreamPerThread>>>(tmX, tmWin, tmW, tmWo, tmY, tmOut, tmWin7, tmWo7, p);
  else fused_kernel<false><<<132, 384, SM_TOTAL, cudaStreamPerThread>>>(tmX, tmWin, tmW, tmWo, tmY, tmOut, tmWin7, tmWo7, p);
}
```

```cpp
#include <cuda_runtime.h>
#include <cuda_bf16.h>
#include <cuda.h>
#include <stdint.h>

namespace {

constexpr int S_ = 2048, D_ = 512, F_ = 1792, FH_ = 896;
#define KV_ST 0
#define CONV_SKEW 0
#define PACE 0
#define YC 1
#define WAITV 1
#define LAG_K 6
#define Y_T 5
#define NPRO 2
#define XS_K 7
constexpr int TILE_B = 28672;

constexpr int SM_TOTAL = 232448;
constexpr int OFF_X = 0;
constexpr int OFF_WR = 131072;
constexpr int G2_ST = 6, G2_STB = 30720;
constexpr int OFF_WO = 61440;
__host__ __device__ constexpr int woslot(int t) { return t < 5 ? OFF_WO + t * 14336 : t == 5 ? 216064 : t == 6 ? 133120 : 90112; }
constexpr int OFF_CV2 = 153600;
constexpr int OFF_YF0 = 61440, OFF_YF1 = 69632, OFF_XF0 = 77824, OFF_XF1 = 104448;
__host__ __device__ constexpr int hslot(int wg, int t) { return ((t & 3) == 0 ? 0 : (t & 3) == 1 ? 28672 : (t & 3) == 2 ? 187264 : 153600) + wg * 14336; }
constexpr int CV_K0 = 0, CV_K1 = 4128, CV_E = 8256, CV_O = 8256 + 2240, CV_CH = 8256 + 4480, CV_PAD = 192;
constexpr int OFF_CV = 205408;
constexpr int OFF_MISC = OFF_CV + 2 * CV_CH;
constexpr int OFF_CS = OFF_MISC;
constexpr int OFF_BAR = OFF_MISC + 960;
constexpr int OFF_EP = OFF_BAR + 8 * 75;
static_assert(OFF_EP + 8 <= SM_TOTAL, "smem");
enum { B_XF = 0, B_WF = 8, B_WE = 24, B_GF = 38, B_GE = 44, B_CS = 50, B_P1 = 51, B_CVF = 52, B_CVA = 54, B_WOF = 55, B_HE = 59,
       B_CVB = 63, B_FX = 64  , B_EP = 66, B_CZ = 67, B_KV = 68, B_KE = 70, B_ZS = 73, B_NUM = 75, B_DUMMY = B_CS  , B_S5 = 36  , B_W0 = 37 };
__host__ __device__ constexpr int hebar(int i) { constexpr int a[10] = {59, 60, 61, 62, 69, 71, 72, 74, 34, 35}; return a[i]; }
__host__ __device__ constexpr unsigned long long hetab() { unsigned long long v = 0; for (int q = 0; q < 8; q++) v |= (unsigned long long)hebar(q) << (8 * q); return v; }
__host__ __device__ constexpr unsigned long long bar2mask(int base) {
  unsigned long long mk = 0;
  for (int q = 0; q < 64; q++) {
    const int i = base + q;
    if (i == B_KE || i == B_P1 || (i >= B_WE && i < B_WE + 10) || (i >= B_GE && i < B_GE + G2_ST) || i == B_CVF || i == B_CVF + 1 || i == B_CVA || i == B_CVB) mk |= 1ull << q;
  }
  return mk;
}
__host__ __device__ constexpr int wslot(int k) { return OFF_WR + (k % 6) * 16384; }
constexpr int ZSLAB = 112 * 1024;

__device__ uint4 g_z2[8 * 16 * TILE_B / 16];
__device__ uint4 g_h[16 * 8 * TILE_B / 16];
__device__ uint4 g_kv[512 * 4096 / 16];
__device__ uint4 g_y[512 * 4096 / 16];
__device__ uint4 g_st[16 * 7 * 128];
__device__ uint4 g_xs[2048];
__device__ uint4 g_cz[448];
__device__ uint2 g_cs[896];
__device__ uint32_t g_cnt[2 * 32];
__device__ uint32_t g_fh[16 * 16 * 8];
__device__ uint32_t g_fk[8 * 16 * 8];
__device__ uint32_t g_epoch;
#define STAMP(i) do {} while (0)
#define STAMPG(i) do {} while (0)

struct Params {
  const __nv_bfloat16 *x, *k, *v, *shift, *ssm_k, *ssm_D, *w_in, *w_sp, *b_sp;
};

__device__ __forceinline__ void fail() { asm volatile("st.global.u32 [%0], %1;" ::"l"(0ULL), "r"(0) : "memory"); }
__device__ __forceinline__ uint32_t smem_u32(const void* p) { return (uint32_t)__cvta_generic_to_shared(p); }
__device__ __forceinline__ void mbar_init(uint32_t bar, int cnt) { asm volatile("mbarrier.init.shared::cta.b64 [%0], %1;" ::"r"(bar), "r"(cnt)); }
__device__ __forceinline__ void mbar_expect_tx(uint32_t bar, uint32_t bytes) { asm volatile("mbarrier.arrive.expect_tx.shared::cta.b64 _, [%0], %1;" ::"r"(bar), "r"(bytes) : "memory"); }
__device__ __forceinline__ void mbar_arrive(uint32_t bar) { asm volatile("mbarrier.arrive.shared::cta.b64 _, [%0];" ::"r"(bar) : "memory"); }
__device__ __forceinline__ void mbar_wait(uint32_t bar, uint32_t par) {
  asm volatile("{\n.reg .pred p;\nLOOP:\n.pragma \"nounroll\";\nmbarrier.try_wait.parity.shared::cta.b64 p, [%0], %1;\n@!p bra.uni LOOP;\n}" ::"r"(bar), "r"(par) : "memory");
}
__device__ __forceinline__ void sched_fence(uint32_t bar) {
  asm volatile("{\n.reg .pred p;\n.reg .b32 n;\nmov.b32 n, 0;\nLOOP:\nadd.u32 n, n, 1;\nmbarrier.test_wait.parity.shared::cta.b64 p, [%0], 0;\n"
               "setp.lt.and.u32 p, n, 4, !p;\n@p bra.uni LOOP;\n}" ::"r"(bar) : "memory");
}
__device__ __forceinline__ void tma2d(uint32_t dst, const CUtensorMap* m, int c0, int c1, uint32_t bar) {
  asm volatile("cp.async.bulk.tensor.2d.shared::cluster.global.mbarrier::complete_tx::bytes [%0], [%1, {%3, %4}], [%2];" ::"r"(dst), "l"(m), "r"(bar), "r"(c0), "r"(c1) : "memory");
}
__device__ __forceinline__ void tma3d(uint32_t dst, const CUtensorMap* m, int c0, int c1, int c2, uint32_t bar) {
  asm volatile("cp.async.bulk.tensor.3d.shared::cluster.global.mbarrier::complete_tx::bytes [%0], [%1, {%3, %4, %5}], [%2];" ::"r"(dst), "l"(m), "r"(bar), "r"(c0), "r"(c1), "r"(c2) : "memory");
}
__device__ __forceinline__ void tma2d_pf(const CUtensorMap* m, int c0, int c1) {
  asm volatile("cp.async.bulk.prefetch.tensor.2d.L2.global.tile [%0, {%1, %2}];" ::"l"(m), "r"(c0), "r"(c1) : "memory");
}
__device__ __forceinline__ void tma2d_st(const CUtensorMap* m, int c0, int c1, uint32_t src) {
  asm volatile("cp.async.bulk.tensor.2d.global.shared::cta.bulk_group [%0, {%1, %2}], [%3];" ::"l"(m), "r"(c0), "r"(c1), "r"(src) : "memory");
}
__device__ __forceinline__ void bulk_g2s(uint32_t dst, const void* src, uint32_t bytes, uint32_t bar) {
  asm volatile("cp.async.bulk.shared::cluster.global.mbarrier::complete_tx::bytes [%0], [%1], %2, [%3];" ::"r"(dst), "l"(src), "r"(bytes), "r"(bar) : "memory");
}
#define ELECT "{\n.reg .pred p;\nelect.sync _|p, 0xffffffff;\n@p "
__device__ __forceinline__ void e_expect(uint32_t bar, uint32_t bytes) { asm volatile(ELECT "mbarrier.arrive.expect_tx.shared::cta.b64 _, [%0], %1;\n}" ::"r"(bar), "r"(bytes) : "memory"); }
__device__ __forceinline__ void e_arrive(uint32_t bar) { asm volatile(ELECT "mbarrier.arrive.shared::cta.b64 _, [%0];\n}" ::"r"(bar) : "memory"); }
__device__ __forceinline__ void e_tma2d(uint32_t dst, const CUtensorMap* m, int c0, int c1, uint32_t bar) {
  asm volatile(ELECT "cp.async.bulk.tensor.2d.shared::cluster.global.mbarrier::complete_tx::bytes [%0], [%1, {%3, %4}], [%2];\n}" ::"r"(dst), "l"(m), "r"(bar), "r"(c0), "r"(c1) : "memory");
}
__device__ __forceinline__ void e_tma3d(uint32_t dst, const CUtensorMap* m, int c0, int c1, int c2, uint32_t bar) {
  asm volatile(ELECT "cp.async.bulk.tensor.3d.shared::cluster.global.mbarrier::complete_tx::bytes [%0], [%1, {%3, %4, %5}], [%2];\n}" ::"r"(dst), "l"(m), "r"(bar), "r"(c0), "r"(c1), "r"(c2) : "memory");
}
__device__ __forceinline__ void e_g2s(uint32_t dst, const void* src, uint32_t bytes, uint32_t bar) {
  asm volatile(ELECT "cp.async.bulk.shared::cluster.global.mbarrier::complete_tx::bytes [%0], [%1], %2, [%3];\n}" ::"r"(dst), "l"(src), "r"(bytes), "r"(bar) : "memory");
}
__device__ __forceinline__ void bulk_s2g(void* dst, uint32_t src, uint32_t bytes) {
  asm volatile("cp.async.bulk.global.shared::cta.bulk_group [%0], [%1], %2;" ::"l"(dst), "r"(src), "r"(bytes) : "memory");
}
__device__ __forceinline__ void bulk_commit() { asm volatile("cp.async.bulk.commit_group;" ::: "memory"); }
template <int N> __device__ __forceinline__ void bulk_wait() { asm volatile("cp.async.bulk.wait_group %0;" ::"n"(N) : "memory"); }
__device__ __forceinline__ void bulk_pf(const void* src, uint32_t bytes) { asm volatile("cp.async.bulk.prefetch.L2.global [%0], %1;" ::"l"(src), "r"(bytes) : "memory"); }
__device__ __forceinline__ void fence_gpu() { asm volatile("fence.acq_rel.gpu;" ::: "memory"); }
__device__ __forceinline__ void st_flag(uint32_t* p, uint32_t v) {
  asm volatile("st.relaxed.gpu.global.v4.u32 [%0], {%1,%1,%1,%1};\nst.relaxed.gpu.global.v4.u32 [%0+16], {%1,%1,%1,%1};" ::"l"(p), "r"(v) : "memory");
}
__device__ __forceinline__ void wg_fence() { asm volatile("wgmma.fence.sync.aligned;" ::: "memory"); }
__device__ __forceinline__ void wg_commit() { asm volatile("wgmma.commit_group.sync.aligned;" ::: "memory"); }
template <int N> __device__ __forceinline__ void wg_wait() { asm volatile("wgmma.wait_group.sync.aligned %0;" ::"n"(N) : "memory"); }
__device__ __forceinline__ uint32_t dlo(uint32_t addr, uint32_t lbo) { return ((addr & 0x3FFFF) >> 4) | ((lbo >> 4) << 16); }
__host__ __device__ constexpr uint32_t dhi(uint32_t sbo, uint32_t swz) { return (sbo >> 4) | (swz << 30); }
__device__ __forceinline__ void bar_sync(int id, int n) { asm volatile("bar.sync %0, %1;" ::"r"(id), "r"(n) : "memory"); }
__device__ __forceinline__ void fence_async_smem() { asm volatile("fence.proxy.async.shared::cta;" ::: "memory"); }
__device__ __forceinline__ void fence_async_glob() { asm volatile("fence.proxy.async.global;" ::: "memory"); }
__device__ __forceinline__ uint32_t ld_acq(const uint32_t* p) { uint32_t v; asm volatile("ld.acquire.gpu.global.u32 %0, [%1];" : "=r"(v) : "l"(p) : "memory"); return v; }
__device__ __forceinline__ uint32_t ld_rlx(const uint32_t* p) { uint32_t v; asm volatile("ld.relaxed.gpu.global.u32 %0, [%1];" : "=r"(v) : "l"(p) : "memory"); return v; }
__device__ __forceinline__ void st_rlx(uint32_t* p, uint32_t v) { asm volatile("st.relaxed.gpu.global.u32 [%0], %1;" ::"l"(p), "r"(v) : "memory"); }
__device__ __forceinline__ uint4 ld_rlx128(const uint4* p) {
  uint4 v;
  asm volatile("{\n.reg .b128 r;\n.reg .b64 a, b;\nld.relaxed.gpu.global.b128 r, [%4];\nmov.b128 {a, b}, r;\nmov.b64 {%0, %1}, a;\nmov.b64 {%2, %3}, b;\n}"
               : "=r"(v.x), "=r"(v.y), "=r"(v.z), "=r"(v.w) : "l"(p) : "memory");
  return v;
}
__device__ __forceinline__ void st_rlx128(uint4* p, uint4 v) {
  asm volatile("{\n.reg .b128 r;\n.reg .b64 a, b;\nmov.b64 a, {%1, %2};\nmov.b64 b, {%3, %4};\nmov.b128 r, {a, b};\nst.relaxed.gpu.global.b128 [%0], r;\n}"
               ::"l"(p), "r"(v.x), "r"(v.y), "r"(v.z), "r"(v.w) : "memory");
}
__device__ __forceinline__ uint2 ld_rlx64(const uint2* p) { unsigned long long v; asm volatile("ld.relaxed.gpu.global.b64 %0, [%1];" : "=l"(v) : "l"(p) : "memory"); return make_uint2((uint32_t)v, (uint32_t)(v >> 32)); }
__device__ __forceinline__ void st_rlx64(uint2* p, uint2 v) { unsigned long long w = (unsigned long long)v.x | ((unsigned long long)v.y << 32); asm volatile("st.relaxed.gpu.global.b64 [%0], %1;" ::"l"(p), "l"(w) : "memory"); }
__device__ __forceinline__ uint4 ldg128(const void* p) { uint4 v; asm volatile("ld.global.nc.L1::no_allocate.v4.u32 {%0,%1,%2,%3}, [%4];" : "=r"(v.x), "=r"(v.y), "=r"(v.z), "=r"(v.w) : "l"(p)); return v; }
__device__ __forceinline__ uint2 ldg64(const void* p) { uint2 v; asm volatile("ld.global.nc.L1::no_allocate.v2.u32 {%0,%1}, [%2];" : "=r"(v.x), "=r"(v.y) : "l"(p)); return v; }
__device__ __forceinline__ uint32_t ldg32(const void* p) { uint32_t v; asm volatile("ld.global.nc.L1::no_allocate.u32 %0, [%1];" : "=r"(v) : "l"(p)); return v; }
__device__ __forceinline__ uint32_t ldg16(const void* p) { unsigned short v; asm volatile("ld.global.nc.u16 %0, [%1];" : "=h"(v) : "l"(p)); return v; }
__device__ __forceinline__ uint32_t lds32(uint32_t a) { uint32_t v; asm volatile("ld.shared.b32 %0, [%1];" : "=r"(v) : "r"(a)); return v; }
__device__ __forceinline__ float2 lds64f(uint32_t a) { float2 v; asm volatile("ld.shared.v2.f32 {%0,%1}, [%2];" : "=f"(v.x), "=f"(v.y) : "r"(a)); return v; }
__device__ __forceinline__ uint4 lds128(uint32_t a) { uint4 v; asm volatile("ld.shared.v4.b32 {%0,%1,%2,%3}, [%4];" : "=r"(v.x), "=r"(v.y), "=r"(v.z), "=r"(v.w) : "r"(a) : "memory"); return v; }
__device__ __forceinline__ void sts128(uint32_t a, uint4 v) { asm volatile("st.shared.v4.b32 [%0], {%1,%2,%3,%4};" ::"r"(a), "r"(v.x), "r"(v.y), "r"(v.z), "r"(v.w) : "memory"); }
__device__ __forceinline__ void ldsm4(uint32_t a, uint32_t (&r)[4]) { asm volatile("ldmatrix.sync.aligned.m8n8.x4.shared.b16 {%0,%1,%2,%3}, [%4];" : "=r"(r[0]), "=r"(r[1]), "=r"(r[2]), "=r"(r[3]) : "r"(a) : "memory"); }
__device__ __forceinline__ void ldsm4t(uint32_t a, uint32_t (&r)[4]) { asm volatile("ldmatrix.sync.aligned.m8n8.x4.trans.shared.b16 {%0,%1,%2,%3}, [%4];" : "=r"(r[0]), "=r"(r[1]), "=r"(r[2]), "=r"(r[3]) : "r"(a) : "memory"); }
__device__ __forceinline__ void stsm4(uint32_t a, uint32_t r0, uint32_t r1, uint32_t r2, uint32_t r3) { asm volatile("stmatrix.sync.aligned.m8n8.x4.shared.b16 [%0], {%1,%2,%3,%4};" ::"r"(a), "r"(r0), "r"(r1), "r"(r2), "r"(r3) : "memory"); }
__device__ __forceinline__ void stsm4t(uint32_t a, uint32_t r0, uint32_t r1, uint32_t r2, uint32_t r3) { asm volatile("stmatrix.sync.aligned.m8n8.x4.trans.shared.b16 [%0], {%1,%2,%3,%4};" ::"r"(a), "r"(r0), "r"(r1), "r"(r2), "r"(r3) : "memory"); }
__device__ __forceinline__ uint32_t pack2(float lo, float hi) { uint32_t r; asm("cvt.rn.bf16x2.f32 %0, %1, %2;" : "=r"(r) : "f"(hi), "f"(lo)); return r; }
__device__ __forceinline__ float blo(uint32_t v) { return __uint_as_float(v << 16); }
__device__ __forceinline__ float bhi(uint32_t v) { return __uint_as_float(v & 0xffff0000u); }
__device__ __forceinline__ uint32_t bmul(uint32_t a, uint32_t b) { uint32_t r; asm("mul.rn.bf16x2 %0, %1, %2;" : "=r"(r) : "r"(a), "r"(b)); return r; }
__device__ __forceinline__ uint32_t badd(uint32_t a, uint32_t b) { uint32_t r; asm("add.rn.bf16x2 %0, %1, %2;" : "=r"(r) : "r"(a), "r"(b)); return r; }
__device__ __forceinline__ uint32_t bfma(uint32_t a, uint32_t b, uint32_t c) { uint32_t r; asm("fma.rn.bf16x2 %0, %1, %2, %3;" : "=r"(r) : "r"(a), "r"(b), "r"(c)); return r; }
__device__ __forceinline__ void mma16816(float (&d)[4], uint32_t a0, uint32_t a1, uint32_t a2, uint32_t a3, uint32_t b0, uint32_t b1) {
  asm volatile("mma.sync.aligned.m16n8k16.row.col.f32.bf16.bf16.f32 {%0,%1,%2,%3}, {%4,%5,%6,%7}, {%8,%9}, {%0,%1,%2,%3};"
               : "+f"(d[0]), "+f"(d[1]), "+f"(d[2]), "+f"(d[3]) : "r"(a0), "r"(a1), "r"(a2), "r"(a3), "r"(b0), "r"(b1));
}
__device__ __forceinline__ float rsq(float x) { float y; asm("rsqrt.approx.ftz.f32 %0, %1;" : "=f"(y) : "f"(x)); return y; }
__device__ __forceinline__ float tanh_(float x) { float y; asm("tanh.approx.f32 %0, %1;" : "=f"(y) : "f"(x)); return y; }
__device__ __forceinline__ float qsum(float v) { v += __shfl_xor_sync(~0u, v, 1); v += __shfl_xor_sync(~0u, v, 2); return v; }
template <int N> __device__ __forceinline__ void zero_acc(float (&d)[N]) {
#pragma unroll
  for (int i = 0; i < N; i++) asm volatile("mov.b32 %0, 0;" : "=f"(d[i]));
}
template <int I> struct IC { static constexpr int v = I; };
template <int B, int E, typename F> __device__ __forceinline__ void sfor(F f) { if constexpr (B < E) { f(IC<B>{}); sfor<B + 1, E>(f); } }

template <int NPER> __device__ __forceinline__ void poll_flags(const uint32_t* base, int n, uint32_t tag, int lane) {
  uint32_t it = 0;
  while (true) {
    bool ok = true;
#pragma unroll
    for (int i = 0; i < NPER; i++) if (lane + 32 * i < n) ok &= (ld_rlx(base + (lane + 32 * i) * 8) == tag);
    if (__all_sync(~0u, ok)) break;
    if (++it > (1u << 20)) fail();
  }
  asm volatile("fence.acquire.gpu;" ::: "memory");
  __syncwarp();
  fence_async_glob();
}
__device__ __forceinline__ void wgmma_ss_n112(float (&d)[56], uint32_t al, uint32_t ah, uint32_t bl, uint32_t bh) {
  asm volatile("{\n.reg .b64 da, db;\nmov.b64 da, {%56, %57};\nmov.b64 db, {%58, %59};\n"
    "wgmma.mma_async.sync.aligned.m64n112k16.f32.bf16.bf16 {%0, %1, %2, %3, %4, %5, %6, %7, %8, %9, %10, %11, %12, %13, %14, %15, %16, %17, %18, %19, %20, %21, %22, %23, %24, %25, %26, %27, %28, %29, %30, %31, %32, %33, %34, %35, %36, %37, %38, %39, %40, %41, %42, %43, %44, %45, %46, %47, %48, %49, %50, %51, %52, %53, %54, %55}, da, db, 1, 1, 1, 0, 1;\n}\n"
    : "+f"(d[0]), "+f"(d[1]), "+f"(d[2]), "+f"(d[3]), "+f"(d[4]), "+f"(d[5]), "+f"(d[6]), "+f"(d[7]), "+f"(d[8]), "+f"(d[9]), "+f"(d[10]), "+f"(d[11]), "+f"(d[12]), "+f"(d[13]), "+f"(d[14]), "+f"(d[15]), "+f"(d[16]), "+f"(d[17]), "+f"(d[18]), "+f"(d[19]), "+f"(d[20]), "+f"(d[21]), "+f"(d[22]), "+f"(d[23]), "+f"(d[24]), "+f"(d[25]), "+f"(d[26]), "+f"(d[27]), "+f"(d[28]), "+f"(d[29]), "+f"(d[30]), "+f"(d[31]), "+f"(d[32]), "+f"(d[33]), "+f"(d[34]), "+f"(d[35]), "+f"(d[36]), "+f"(d[37]), "+f"(d[38]), "+f"(d[39]), "+f"(d[40]), "+f"(d[41]), "+f"(d[42]), "+f"(d[43]), "+f"(d[44]), "+f"(d[45]), "+f"(d[46]), "+f"(d[47]), "+f"(d[48]), "+f"(d[49]), "+f"(d[50]), "+f"(d[51]), "+f"(d[52]), "+f"(d[53]), "+f"(d[54]), "+f"(d[55])
    : "r"(al), "r"(ah), "r"(bl), "r"(bh));
}
__device__ __forceinline__ void wgmma_ss_n128(float (&d)[64], uint32_t al, uint32_t ah, uint32_t bl, uint32_t bh) {
  asm volatile("{\n.reg .b64 da, db;\nmov.b64 da, {%64, %65};\nmov.b64 db, {%66, %67};\n"
    "wgmma.mma_async.sync.aligned.m64n128k16.f32.bf16.bf16 {%0, %1, %2, %3, %4, %5, %6, %7, %8, %9, %10, %11, %12, %13, %14, %15, %16, %17, %18, %19, %20, %21, %22, %23, %24, %25, %26, %27, %28, %29, %30, %31, %32, %33, %34, %35, %36, %37, %38, %39, %40, %41, %42, %43, %44, %45, %46, %47, %48, %49, %50, %51, %52, %53, %54, %55, %56, %57, %58, %59, %60, %61, %62, %63}, da, db, 1, 1, 1, 0, 1;\n}\n"
    : "+f"(d[0]), "+f"(d[1]), "+f"(d[2]), "+f"(d[3]), "+f"(d[4]), "+f"(d[5]), "+f"(d[6]), "+f"(d[7]), "+f"(d[8]), "+f"(d[9]), "+f"(d[10]), "+f"(d[11]), "+f"(d[12]), "+f"(d[13]), "+f"(d[14]), "+f"(d[15]), "+f"(d[16]), "+f"(d[17]), "+f"(d[18]), "+f"(d[19]), "+f"(d[20]), "+f"(d[21]), "+f"(d[22]), "+f"(d[23]), "+f"(d[24]), "+f"(d[25]), "+f"(d[26]), "+f"(d[27]), "+f"(d[28]), "+f"(d[29]), "+f"(d[30]), "+f"(d[31]), "+f"(d[32]), "+f"(d[33]), "+f"(d[34]), "+f"(d[35]), "+f"(d[36]), "+f"(d[37]), "+f"(d[38]), "+f"(d[39]), "+f"(d[40]), "+f"(d[41]), "+f"(d[42]), "+f"(d[43]), "+f"(d[44]), "+f"(d[45]), "+f"(d[46]), "+f"(d[47]), "+f"(d[48]), "+f"(d[49]), "+f"(d[50]), "+f"(d[51]), "+f"(d[52]), "+f"(d[53]), "+f"(d[54]), "+f"(d[55]), "+f"(d[56]), "+f"(d[57]), "+f"(d[58]), "+f"(d[59]), "+f"(d[60]), "+f"(d[61]), "+f"(d[62]), "+f"(d[63])
    : "r"(al), "r"(ah), "r"(bl), "r"(bh));
}
__device__ __forceinline__ void wgmma_ss_n64(float (&d)[32], uint32_t al, uint32_t ah, uint32_t bl, uint32_t bh) {
  asm volatile("{\n.reg .b64 da, db;\nmov.b64 da, {%32, %33};\nmov.b64 db, {%34, %35};\n"
    "wgmma.mma_async.sync.aligned.m64n64k16.f32.bf16.bf16 {%0, %1, %2, %3, %4, %5, %6, %7, %8, %9, %10, %11, %12, %13, %14, %15, %16, %17, %18, %19, %20, %21, %22, %23, %24, %25, %26, %27, %28, %29, %30, %31}, da, db, 1, 1, 1, 0, 1;\n}\n"
    : "+f"(d[0]), "+f"(d[1]), "+f"(d[2]), "+f"(d[3]), "+f"(d[4]), "+f"(d[5]), "+f"(d[6]), "+f"(d[7]), "+f"(d[8]), "+f"(d[9]), "+f"(d[10]), "+f"(d[11]), "+f"(d[12]), "+f"(d[13]), "+f"(d[14]), "+f"(d[15]), "+f"(d[16]), "+f"(d[17]), "+f"(d[18]), "+f"(d[19]), "+f"(d[20]), "+f"(d[21]), "+f"(d[22]), "+f"(d[23]), "+f"(d[24]), "+f"(d[25]), "+f"(d[26]), "+f"(d[27]), "+f"(d[28]), "+f"(d[29]), "+f"(d[30]), "+f"(d[31])
    : "r"(al), "r"(ah), "r"(bl), "r"(bh));
}
template <int N> __device__ __forceinline__ void wgmma_cv(float (&d)[64], uint32_t a0, uint32_t a1, uint32_t a2, uint32_t a3, uint32_t bl);
template <> __device__ __forceinline__ void wgmma_cv<16>(float (&d)[64], uint32_t a0, uint32_t a1, uint32_t a2, uint32_t a3, uint32_t bl) {
  asm volatile("{\n.reg .b64 db;\nmov.b64 db, {%12, 8};\n"
    "wgmma.mma_async.sync.aligned.m64n16k16.f32.bf16.bf16 {%0, %1, %2, %3, %4, %5, %6, %7}, {%8, %9, %10, %11}, db, 1, 1, 1, 0;\n}\n"
    : "+f"(d[56]), "+f"(d[57]), "+f"(d[58]), "+f"(d[59]), "+f"(d[60]), "+f"(d[61]), "+f"(d[62]), "+f"(d[63])
    : "r"(a0), "r"(a1), "r"(a2), "r"(a3), "r"(bl));
}
template <> __device__ __forceinline__ void wgmma_cv<32>(float (&d)[64], uint32_t a0, uint32_t a1, uint32_t a2, uint32_t a3, uint32_t bl) {
  asm volatile("{\n.reg .b64 db;\nmov.b64 db, {%20, 8};\n"
    "wgmma.mma_async.sync.aligned.m64n32k16.f32.bf16.bf16 {%0, %1, %2, %3, %4, %5, %6, %7, %8, %9, %10, %11, %12, %13, %14, %15}, {%16, %17, %18, %19}, db, 1, 1, 1, 0;\n}\n"
    : "+f"(d[48]), "+f"(d[49]), "+f"(d[50]), "+f"(d[51]), "+f"(d[52]), "+f"(d[53]), "+f"(d[54]), "+f"(d[55]), "+f"(d[56]), "+f"(d[57]), "+f"(d[58]), "+f"(d[59]), "+f"(d[60]), "+f"(d[61]), "+f"(d[62]), "+f"(d[63])
    : "r"(a0), "r"(a1), "r"(a2), "r"(a3), "r"(bl));
}
template <> __device__ __forceinline__ void wgmma_cv<48>(float (&d)[64], uint32_t a0, uint32_t a1, uint32_t a2, uint32_t a3, uint32_t bl) {
  asm volatile("{\n.reg .b64 db;\nmov.b64 db, {%28, 8};\n"
    "wgmma.mma_async.sync.aligned.m64n48k16.f32.bf16.bf16 {%0, %1, %2, %3, %4, %5, %6, %7, %8, %9, %10, %11, %12, %13, %14, %15, %16, %17, %18, %19, %20, %21, %22, %23}, {%24, %25, %26, %27}, db, 1, 1, 1, 0;\n}\n"
    : "+f"(d[40]), "+f"(d[41]), "+f"(d[42]), "+f"(d[43]), "+f"(d[44]), "+f"(d[45]), "+f"(d[46]), "+f"(d[47]), "+f"(d[48]), "+f"(d[49]), "+f"(d[50]), "+f"(d[51]), "+f"(d[52]), "+f"(d[53]), "+f"(d[54]), "+f"(d[55]), "+f"(d[56]), "+f"(d[57]), "+f"(d[58]), "+f"(d[59]), "+f"(d[60]), "+f"(d[61]), "+f"(d[62]), "+f"(d[63])
    : "r"(a0), "r"(a1), "r"(a2), "r"(a3), "r"(bl));
}
template <> __device__ __forceinline__ void wgmma_cv<64>(float (&d)[64], uint32_t a0, uint32_t a1, uint32_t a2, uint32_t a3, uint32_t bl) {
  asm volatile("{\n.reg .b64 db;\nmov.b64 db, {%36, 8};\n"
    "wgmma.mma_async.sync.aligned.m64n64k16.f32.bf16.bf16 {%0, %1, %2, %3, %4, %5, %6, %7, %8, %9, %10, %11, %12, %13, %14, %15, %16, %17, %18, %19, %20, %21, %22, %23, %24, %25, %26, %27, %28, %29, %30, %31}, {%32, %33, %34, %35}, db, 1, 1, 1, 0;\n}\n"
    : "+f"(d[32]), "+f"(d[33]), "+f"(d[34]), "+f"(d[35]), "+f"(d[36]), "+f"(d[37]), "+f"(d[38]), "+f"(d[39]), "+f"(d[40]), "+f"(d[41]), "+f"(d[42]), "+f"(d[43]), "+f"(d[44]), "+f"(d[45]), "+f"(d[46]), "+f"(d[47]), "+f"(d[48]), "+f"(d[49]), "+f"(d[50]), "+f"(d[51]), "+f"(d[52]), "+f"(d[53]), "+f"(d[54]), "+f"(d[55]), "+f"(d[56]), "+f"(d[57]), "+f"(d[58]), "+f"(d[59]), "+f"(d[60]), "+f"(d[61]), "+f"(d[62]), "+f"(d[63])
    : "r"(a0), "r"(a1), "r"(a2), "r"(a3), "r"(bl));
}
template <> __device__ __forceinline__ void wgmma_cv<80>(float (&d)[64], uint32_t a0, uint32_t a1, uint32_t a2, uint32_t a3, uint32_t bl) {
  asm volatile("{\n.reg .b64 db;\nmov.b64 db, {%44, 8};\n"
    "wgmma.mma_async.sync.aligned.m64n80k16.f32.bf16.bf16 {%0, %1, %2, %3, %4, %5, %6, %7, %8, %9, %10, %11, %12, %13, %14, %15, %16, %17, %18, %19, %20, %21, %22, %23, %24, %25, %26, %27, %28, %29, %30, %31, %32, %33, %34, %35, %36, %37, %38, %39}, {%40, %41, %42, %43}, db, 1, 1, 1, 0;\n}\n"
    : "+f"(d[24]), "+f"(d[25]), "+f"(d[26]), "+f"(d[27]), "+f"(d[28]), "+f"(d[29]), "+f"(d[30]), "+f"(d[31]), "+f"(d[32]), "+f"(d[33]), "+f"(d[34]), "+f"(d[35]), "+f"(d[36]), "+f"(d[37]), "+f"(d[38]), "+f"(d[39]), "+f"(d[40]), "+f"(d[41]), "+f"(d[42]), "+f"(d[43]), "+f"(d[44]), "+f"(d[45]), "+f"(d[46]), "+f"(d[47]), "+f"(d[48]), "+f"(d[49]), "+f"(d[50]), "+f"(d[51]), "+f"(d[52]), "+f"(d[53]), "+f"(d[54]), "+f"(d[55]), "+f"(d[56]), "+f"(d[57]), "+f"(d[58]), "+f"(d[59]), "+f"(d[60]), "+f"(d[61]), "+f"(d[62]), "+f"(d[63])
    : "r"(a0), "r"(a1), "r"(a2), "r"(a3), "r"(bl));
}
template <> __device__ __forceinline__ void wgmma_cv<96>(float (&d)[64], uint32_t a0, uint32_t a1, uint32_t a2, uint32_t a3, uint32_t bl) {
  asm volatile("{\n.reg .b64 db;\nmov.b64 db, {%52, 8};\n"
    "wgmma.mma_async.sync.aligned.m64n96k16.f32.bf16.bf16 {%0, %1, %2, %3, %4, %5, %6, %7, %8, %9, %10, %11, %12, %13, %14, %15, %16, %17, %18, %19, %20, %21, %22, %23, %24, %25, %26, %27, %28, %29, %30, %31, %32, %33, %34, %35, %36, %37, %38, %39, %40, %41, %42, %43, %44, %45, %46, %47}, {%48, %49, %50, %51}, db, 1, 1, 1, 0;\n}\n"
    : "+f"(d[16]), "+f"(d[17]), "+f"(d[18]), "+f"(d[19]), "+f"(d[20]), "+f"(d[21]), "+f"(d[22]), "+f"(d[23]), "+f"(d[24]), "+f"(d[25]), "+f"(d[26]), "+f"(d[27]), "+f"(d[28]), "+f"(d[29]), "+f"(d[30]), "+f"(d[31]), "+f"(d[32]), "+f"(d[33]), "+f"(d[34]), "+f"(d[35]), "+f"(d[36]), "+f"(d[37]), "+f"(d[38]), "+f"(d[39]), "+f"(d[40]), "+f"(d[41]), "+f"(d[42]), "+f"(d[43]), "+f"(d[44]), "+f"(d[45]), "+f"(d[46]), "+f"(d[47]), "+f"(d[48]), "+f"(d[49]), "+f"(d[50]), "+f"(d[51]), "+f"(d[52]), "+f"(d[53]), "+f"(d[54]), "+f"(d[55]), "+f"(d[56]), "+f"(d[57]), "+f"(d[58]), "+f"(d[59]), "+f"(d[60]), "+f"(d[61]), "+f"(d[62]), "+f"(d[63])
    : "r"(a0), "r"(a1), "r"(a2), "r"(a3), "r"(bl));
}
template <> __device__ __forceinline__ void wgmma_cv<112>(float (&d)[64], uint32_t a0, uint32_t a1, uint32_t a2, uint32_t a3, uint32_t bl) {
  asm volatile("{\n.reg .b64 db;\nmov.b64 db, {%60, 8};\n"
    "wgmma.mma_async.sync.aligned.m64n112k16.f32.bf16.bf16 {%0, %1, %2, %3, %4, %5, %6, %7, %8, %9, %10, %11, %12, %13, %14, %15, %16, %17, %18, %19, %20, %21, %22, %23, %24, %25, %26, %27, %28, %29, %30, %31, %32, %33, %34, %35, %36, %37, %38, %39, %40, %41, %42, %43, %44, %45, %46, %47, %48, %49, %50, %51, %52, %53, %54, %55}, {%56, %57, %58, %59}, db, 1, 1, 1, 0;\n}\n"
    : "+f"(d[8]), "+f"(d[9]), "+f"(d[10]), "+f"(d[11]), "+f"(d[12]), "+f"(d[13]), "+f"(d[14]), "+f"(d[15]), "+f"(d[16]), "+f"(d[17]), "+f"(d[18]), "+f"(d[19]), "+f"(d[20]), "+f"(d[21]), "+f"(d[22]), "+f"(d[23]), "+f"(d[24]), "+f"(d[25]), "+f"(d[26]), "+f"(d[27]), "+f"(d[28]), "+f"(d[29]), "+f"(d[30]), "+f"(d[31]), "+f"(d[32]), "+f"(d[33]), "+f"(d[34]), "+f"(d[35]), "+f"(d[36]), "+f"(d[37]), "+f"(d[38]), "+f"(d[39]), "+f"(d[40]), "+f"(d[41]), "+f"(d[42]), "+f"(d[43]), "+f"(d[44]), "+f"(d[45]), "+f"(d[46]), "+f"(d[47]), "+f"(d[48]), "+f"(d[49]), "+f"(d[50]), "+f"(d[51]), "+f"(d[52]), "+f"(d[53]), "+f"(d[54]), "+f"(d[55]), "+f"(d[56]), "+f"(d[57]), "+f"(d[58]), "+f"(d[59]), "+f"(d[60]), "+f"(d[61]), "+f"(d[62]), "+f"(d[63])
    : "r"(a0), "r"(a1), "r"(a2), "r"(a3), "r"(bl));
}
template <> __device__ __forceinline__ void wgmma_cv<128>(float (&d)[64], uint32_t a0, uint32_t a1, uint32_t a2, uint32_t a3, uint32_t bl) {
  asm volatile("{\n.reg .b64 db;\nmov.b64 db, {%68, 8};\n"
    "wgmma.mma_async.sync.aligned.m64n128k16.f32.bf16.bf16 {%0, %1, %2, %3, %4, %5, %6, %7, %8, %9, %10, %11, %12, %13, %14, %15, %16, %17, %18, %19, %20, %21, %22, %23, %24, %25, %26, %27, %28, %29, %30, %31, %32, %33, %34, %35, %36, %37, %38, %39, %40, %41, %42, %43, %44, %45, %46, %47, %48, %49, %50, %51, %52, %53, %54, %55, %56, %57, %58, %59, %60, %61, %62, %63}, {%64, %65, %66, %67}, db, 1, 1, 1, 0;\n}\n"
    : "+f"(d[0]), "+f"(d[1]), "+f"(d[2]), "+f"(d[3]), "+f"(d[4]), "+f"(d[5]), "+f"(d[6]), "+f"(d[7]), "+f"(d[8]), "+f"(d[9]), "+f"(d[10]), "+f"(d[11]), "+f"(d[12]), "+f"(d[13]), "+f"(d[14]), "+f"(d[15]), "+f"(d[16]), "+f"(d[17]), "+f"(d[18]), "+f"(d[19]), "+f"(d[20]), "+f"(d[21]), "+f"(d[22]), "+f"(d[23]), "+f"(d[24]), "+f"(d[25]), "+f"(d[26]), "+f"(d[27]), "+f"(d[28]), "+f"(d[29]), "+f"(d[30]), "+f"(d[31]), "+f"(d[32]), "+f"(d[33]), "+f"(d[34]), "+f"(d[35]), "+f"(d[36]), "+f"(d[37]), "+f"(d[38]), "+f"(d[39]), "+f"(d[40]), "+f"(d[41]), "+f"(d[42]), "+f"(d[43]), "+f"(d[44]), "+f"(d[45]), "+f"(d[46]), "+f"(d[47]), "+f"(d[48]), "+f"(d[49]), "+f"(d[50]), "+f"(d[51]), "+f"(d[52]), "+f"(d[53]), "+f"(d[54]), "+f"(d[55]), "+f"(d[56]), "+f"(d[57]), "+f"(d[58]), "+f"(d[59]), "+f"(d[60]), "+f"(d[61]), "+f"(d[62]), "+f"(d[63])
    : "r"(a0), "r"(a1), "r"(a2), "r"(a3), "r"(bl));
}

struct RowC { float nmu, a, b; };
__device__ __forceinline__ float gelu_f(float acc, float cs, const RowC& c) {
  float t = fmaf(c.nmu, cs, acc);
  float u = t * fmaf(t * t, c.b, c.a);
  return fmaf(t, tanh_(u), t);
}

template <typename F> __device__ __forceinline__ void conv_mma(uint32_t cv, uint32_t pw, int w, int lane, F shadow) {
  const int g = lane >> 2, tq = lane & 3;
  float d[64];
  zero_acc(d);
  const uint32_t abase = cv + ((g & 1) ? (CV_K0 + 2 * (16 + 16 * w + g - 2 * tq - 1)) : (CV_K1 + 2 * (16 + 16 * w + g - 2 * tq)));
  const uint32_t dbase = dlo(cv + CV_E + CV_PAD, CV_O - CV_E);
  const int mi = lane >> 3, rr = lane & 7;
  const uint32_t paddr = pw + 16 * ((2 * ((mi >> 1) * 8 + rr + w) + (mi & 1)) ^ (((rr + w) >> 2) & 1));
  uint32_t a[32][3];
  auto loadA = [&](auto bi) {
    constexpr int b = decltype(bi)::v;
    if constexpr (b < 8) {
#pragma unroll
      for (int s = 0; s < 4; s++) {
        const int st = 4 * b + s;
        a[st][0] = lds32(abase + 128 * st); a[st][1] = lds32(abase + 128 * st + 16); a[st][2] = lds32(abase + 128 * st - 16);
      }
    }
  };
  loadA(IC<0>{});
  sfor<0, 8>([&](auto ii) {
    constexpr int b = decltype(ii)::v;
    wg_fence();
    sfor<0, 4>([&](auto ss) {
      constexpr int st = 4 * b + decltype(ss)::v;
      wgmma_cv<128 - 16 * b>(d, a[st][0], a[st][1], a[st][2], a[st][0], dbase - (4 * st - 16 * b));
    });
    wg_commit();
    loadA(IC<b + 1>{});
    if constexpr (b == 0) shadow();
    if constexpr (b > 0) {
      constexpr int i = 2 * (b - 1);
      stsm4t(paddr + i * 256, pack2(d[4 * i], d[4 * i + 1]), pack2(d[4 * i + 2], d[4 * i + 3]), pack2(d[4 * i + 4], d[4 * i + 5]), pack2(d[4 * i + 6], d[4 * i + 7]));
    }
    wg_wait<0>();
#pragma unroll
    for (int i = 8 * b; i < 64; i++) { float tmp; asm volatile("mov.b32 %0, %1;" : "=f"(tmp) : "f"(d[i])); d[i] = tmp; }
  });
  stsm4t((mi >= 2 && rr + w >= 8) ? pw + 16 * (mi & 1) : paddr + 14 * 256, pack2(d[56], d[57]), pack2(d[58], d[59]), pack2(d[60], d[61]), pack2(d[62], d[63]));
}
__device__ __forceinline__ void conv_fin(uint32_t cv, const uint32_t (&pq)[4], int t, uint32_t D2, uint4* yrow) {
#pragma unroll
  for (int h = 0; h < 2; h++) {
    const int c = h * 128 + t;
    const uint4 u = lds128(cv + ((c & 1) ? CV_O : CV_E) + CV_PAD + (c >> 1) * 16);
    uint4 v[4];
#pragma unroll
    for (int q = 0; q < 4; q++) {
      v[q] = lds128(pq[q] + 16 * (c ^ ((c >> 3) & 1)));
      if (h == 0 && c < 2 * q) v[q] = make_uint4(0, 0, 0, 0);
    }
    auto f = [&](uint32_t a, uint32_t b, uint32_t cc, uint32_t d, uint32_t uu) { return bfma(__byte_perm(uu, uu, 0x1032), D2, badd(badd(a, b), badd(cc, d))); };
    st_rlx128(yrow + c, make_uint4(f(v[0].x, v[1].x, v[2].x, v[3].x, u.x), f(v[0].y, v[1].y, v[2].y, v[3].y, u.y),
                                           f(v[0].z, v[1].z, v[2].z, v[3].z, u.z), f(v[0].w, v[1].w, v[2].w, v[3].w, u.w)));
  }
}

template <bool SMID> __global__ void __launch_bounds__(384, 1)
fused_kernel(const __grid_constant__ CUtensorMap tmX, const __grid_constant__ CUtensorMap tmWin, const __grid_constant__ CUtensorMap tmW,
             const __grid_constant__ CUtensorMap tmWo, const __grid_constant__ CUtensorMap tmOut,
             const __grid_constant__ CUtensorMap tmWin7, const __grid_constant__ CUtensorMap tmWo7, const __grid_constant__ CUtensorMap tmXh,
             const Params p) {
  extern __shared__ __align__(1024) uint8_t smraw[];
  const uint32_t sb = smem_u32(smraw);
  const int tid = threadIdx.x, warp = __shfl_sync(~0u, tid >> 5, 0), lane = tid & 31;
  int m, j;
  {
    int G, jj;
    if (SMID) {
      uint32_t smid; asm("mov.u32 %0, %%smid;" : "=r"(smid));
      if (smid < 64) { G = (smid >> 1) & 7; jj = (smid >> 4) * 2 + (smid & 1); }
      else if (smid < 120) { int t = (smid - 64) >> 1; G = 1 + t % 7; jj = 8 + (t / 7) * 2 + (smid & 1); }
      else if (smid < 124) { G = -1; jj = smid - 120; }
      else { G = 0; jj = 8 + (smid - 124); if (smid > 131) fail(); }
    } else if (blockIdx.x < 4) { G = -1; jj = blockIdx.x; }
    else { G = (blockIdx.x - 4) >> 4; jj = (blockIdx.x - 4) & 15; }
    if (G < 0) {
      const uint32_t tag = *(volatile uint32_t*)&g_epoch + 1;
      const int nb = jj < 3 ? 4 : 2;
      if (tid < nb * 64) st_rlx64(g_cs + jj * 256 + tid, make_uint2(0, 0));
      const uint32_t sbar = sb + OFF_BAR;
      auto load = [&](int k) {
        mbar_expect_tx(sbar + 8 * k, nb * 8192);
#pragma unroll 1
        for (int b = 0; b < nb; b++) tma2d(sb + (k % 6) * 32768 + b * 8192, &tmWin, jj * 256 + b * 64, k * 64, sbar + 8 * k);
      };
      if (tid == 0) {
        for (int k = 0; k < 8; k++) mbar_init(sbar + 8 * k, 1);
        asm volatile("fence.mbarrier_init.release.cluster;" ::: "memory");
        fence_async_smem();
#pragma unroll 1
        for (int k = 0; k < 6; k++) load(k);
      }
      __syncthreads();
      float acc[8] = {0, 0, 0, 0, 0, 0, 0, 0};
#pragma unroll 1
      for (int k = 0; k < 8; k++) {
        if (warp < 8) {
          mbar_wait(sbar + 8 * k, 0);
#pragma unroll
          for (int i = 0; i < 8; i++) {
            const uint4 v = lds128(sb + (k % 6) * 32768 + (lane >> 3) * 8192 + (warp + 8 * i) * 128 + (((lane & 7) ^ warp) << 4));
            acc[0] += blo(v.x); acc[1] += bhi(v.x); acc[2] += blo(v.y); acc[3] += bhi(v.y);
            acc[4] += blo(v.z); acc[5] += bhi(v.z); acc[6] += blo(v.w); acc[7] += bhi(v.w);
          }
        }
        if (k == 1) { __syncthreads(); if (tid == 0) {
#pragma unroll 1
          for (int q = 6; q < 8; q++) load(q);
        } }
      }
      float* ps = (float*)(smraw + 196608);
      if (warp < 8) {
#pragma unroll
        for (int e = 0; e < 8; e++) ps[warp * 256 + lane * 8 + e] = acc[e];
      }
      __syncthreads();
      if (tid < nb * 64) {
        float s = 0;
#pragma unroll
        for (int q = 0; q < 8; q++) s += ps[q * 256 + tid];
        st_rlx64(g_cs + jj * 256 + tid, make_uint2(__float_as_uint(s), tag));
      }
      if (tid == 0) STAMP(50);
      if (warp == 0)
#pragma unroll 1
        for (int it = 0; it < 400; it++) { if (ld_rlx(g_cnt + (tag & 1) * 32) >= 112) break; __nanosleep(200); }
      return;
    }
    m = (G >> 1) * 4 + (jj >> 2); j = (G & 1) * 4 + (jj & 3);
  }
  const uint32_t bars = sb + OFF_BAR;
#define BAR(i) (bars + 8 * (i))
  const bool dz2 = j < 7;
  auto init_others = [&]() {
    if (lane == 0) {
      auto init_range = [&](auto lo, auto hi) {
        sfor<decltype(lo)::v, decltype(hi)::v>([&](auto ii) {
          constexpr int i = decltype(ii)::v;
          mbar_init(BAR(i), i == B_ZS ? 3 : 1 + (int)((bar2mask(i & 64) >> (i & 63)) & 1));
        });
      };
      if (warp == 9) { init_range(IC<NPRO>{}, IC<8>{}); init_range(IC<8 + NPRO>{}, IC<24>{}); }
      else if (warp == 10) init_range(IC<24>{}, IC<50>{});
      else init_range(IC<50>{}, IC<B_NUM>{});
      asm volatile("fence.mbarrier_init.release.cluster;" ::: "memory");
    }
    __syncwarp();
    asm volatile("bar.arrive 5, 128;" ::: "memory");
  };

  if (warp < 8) {
    asm volatile("setmaxnreg.inc.sync.aligned.u32 200;");
    bar_sync(4, 384);
    if (tid == 0) STAMP(30);
    const int wg = warp >> 2, w = warp & 3, g = lane >> 2, tq = lane & 3, t = tid & 127;
    const bool el = (t == 0);
    const int row0 = wg * 64 + w * 16 + g;
    const int lr = wg * 64 + w * 16 + (lane & 7) + ((lane >> 3) & 1) * 8;
    const uint32_t lrow = lr * 128, lsw = lane & 7, lhi = lane >> 4;

    float z2[64], z1[56];
    constexpr uint32_t H128 = dhi(1024, 1);
    const uint32_t dX = dlo(sb + OFF_X + wg * 8192, 16), dW = dlo(sb, 8192);
    const uint32_t dW1 = dz2 ? dW : dlo(sb, 2048), hW1 = dz2 ? H128 : dhi(256, 3), stepW1 = dz2 ? 128 : 32;
    auto z1_issue = [&](auto kc) {
      constexpr int k = decltype(kc)::v;
      mbar_wait(BAR(B_WF + k), 0);
      wg_fence();
#pragma unroll
      for (int kk = 0; kk < 4; kk++) wgmma_ss_n112(z1, dX + (k & 7) * 1024 + kk * 2, H128, dW1 + wslot(k) / 16 + kk * stepW1, hW1);
      wg_commit();
      if constexpr (k <= 10) sched_fence(BAR(B_WF + k));
    };
    if (!dz2) {
      constexpr uint32_t ONE2 = 0x3F803F80u;
      uint4* czp = g_cz + m * 32 + lane;
      if (warp == 0 && m < 14) st_rlx128(czp, make_uint4(0, 0, 0, 0));
      if (tq < 2) st_rlx128(g_xs + m * 128 + row0 + tq * 8, make_uint4(0, 0, 0, 0));
      mbar_wait(BAR(B_EP), 0);
      const uint32_t tg = lds32(sb + OFF_EP);
      float d1[4][4], d2[4][4], d3[4][4];
#pragma unroll
      for (int i = 0; i < 4; i++) { d1[i][0] = d1[i][1] = d1[i][2] = d1[i][3] = 0.f; d2[i][0] = d2[i][1] = d2[i][2] = d2[i][3] = 0.f; d3[i][0] = d3[i][1] = d3[i][2] = d3[i][3] = 0.f; }
      uint32_t xa[4];
#pragma unroll
      for (int kk = 0; kk < 4; kk++) xa[kk] = sb + OFF_X + lrow + (((2 * kk + lhi) ^ lsw) << 4);
      auto xgrp = [&](int k0) {
        mbar_wait(BAR(B_XF + k0), 0); mbar_wait(BAR(B_XF + k0 + 1), 0);
        uint32_t r[8][4];
#pragma unroll
        for (int i = 0; i < 8; i++) ldsm4(xa[i & 3] + (k0 + (i >> 2)) * 16384, r[i]);
#pragma unroll
        for (int i = 0; i < 8; i++) {
          mma16816(d1[i & 3], r[i][0], r[i][1], r[i][2], r[i][3], r[i][0], r[i][2]);
          mma16816(d2[i & 3], r[i][0], r[i][1], r[i][2], r[i][3], r[i][1], r[i][3]);
          mma16816(d3[i & 3], r[i][0], r[i][1], r[i][2], r[i][3], ONE2, ONE2);
        }
      };
      xgrp(0); xgrp(2); xgrp(4);
      if (m < 14) {
        mbar_wait(BAR(B_WF), 0);
        float cs[8][4];
#pragma unroll
        for (int i = 0; i < 8; i++) cs[i][0] = cs[i][1] = cs[i][2] = cs[i][3] = 0.f;
        const uint32_t ba = sb + OFF_WR + warp * 8192 + (lane & 15) * 128;
#pragma unroll
        for (int kk = 0; kk < 4; kk++) {
#pragma unroll
          for (int i = 0; i < 8; i += 2) {
            uint32_t r[4];
            ldsm4t(ba + kk * 2048 + (((i + lhi) ^ lsw) << 4), r);
            mma16816(cs[i], ONE2, ONE2, ONE2, ONE2, r[0], r[1]);
            mma16816(cs[i + 1], ONE2, ONE2, ONE2, ONE2, r[2], r[3]);
          }
        }
        float a = cs[0][0], b = cs[0][1];
#pragma unroll
        for (int i = 1; i < 8; i++) if (g == i) { a = cs[i][0]; b = cs[i][1]; }
        asm volatile("st.shared.v2.f32 [%0], {%1, %2};" ::"r"(sb + 196608 + warp * 256 + lane * 8), "f"(a), "f"(b) : "memory");
      }
      bar_sync(3, 256);
      if (warp == 0 && m < 14) {
        float a = 0, b = 0;
#pragma unroll
        for (int q = 0; q < 8; q++) { const float2 v = lds64f(sb + 196608 + q * 256 + lane * 8); a += v.x; b += v.y; }
        st_rlx128(czp, make_uint4(__float_as_uint(a), __float_as_uint(b), tg, 0));
      }
      if (el) for (int k = 0; k < 7; k++) if (k != 4 || wg) mbar_arrive(BAR(B_WE + k));
      if (tid == 0) mbar_arrive(BAR(B_WE + 4));
      if (tid == 0) STAMP(40);
      xgrp(6);
      const int ga = g & 1;
      const float qa = __shfl_sync(~0u, ga ? d1[0][1] + d1[1][1] + d1[2][1] + d1[3][1] : d1[0][0] + d1[1][0] + d1[2][0] + d1[3][0], g * 4 + (g >> 1));
      const float qb = __shfl_sync(~0u, ga ? d2[0][3] + d2[1][3] + d2[2][3] + d2[3][3] : d2[0][2] + d2[1][2] + d2[2][2] + d2[3][2], g * 4 + (g >> 1));
      const float mu = (tq ? d3[0][2] + d3[1][2] + d3[2][2] + d3[3][2] : d3[0][0] + d3[1][0] + d3[2][0] + d3[3][0]) * (1.f / 512);
      const float ve = fmaxf((tq ? qb : qa) * (1.f / 512) - mu * mu, 0.f) + 1e-5f, rs = rsqrtf(ve);
      if (tq < 2) st_rlx128(g_xs + m * 128 + row0 + tq * 8, make_uint4(__float_as_uint(mu), __float_as_uint(rs), tg, __float_as_uint(4e-5f * ve)));
      if (tid == 0) STAMP(37);
    }
    zero_acc(z2); zero_acc(z1);
    if (tid == 0) STAMP(1);
    uint4 xs0, xs1;
    if (dz2) {
      uint32_t da = dX, db = dW + OFF_WR / 16;
#pragma unroll 1
      for (int k = 0; k < 8; k++) {
        mbar_wait(BAR(B_XF + k), 0);
        mbar_wait(BAR(B_WF + k), 0);
        if (k == LAG_K && wg) mbar_wait(BAR(B_W0), 0);
        wg_fence();
#pragma unroll
        for (int kk = 0; kk < 4; kk++) wgmma_ss_n128(z2, da + kk * 2, H128, db + kk * 128, H128);
        wg_commit();
        if (k == 0 && tq < 2) st_rlx128(g_st + (m * 7 + j) * 128 + row0 + tq * 8, make_uint4(0, 0, 0, 0));
        da += 1024; db = k == 5 ? dW + OFF_WR / 16 : db + 1024;
        if (k == 7 && tid == 0) mbar_arrive(BAR(B_W0));
        if (k == 7) break;
        wg_wait<1>();
        if (k > 0 && el) mbar_arrive(BAR(B_WE + k - 1));
      }
    }
    xs0 = ld_rlx128(g_xs + m * 128 + row0); xs1 = ld_rlx128(g_xs + m * 128 + row0 + 8);
    wg_wait<1>();
    if (dz2 && el) mbar_arrive(BAR(B_WE + 6));
    z1_issue(IC<8>{});
    mbar_wait(BAR(B_EP), 0);
    const uint32_t tag = lds32(sb + OFF_EP);
    float mu0, rs0, mu1, rs1, ep0, ep1;
    {
      uint4 v0 = xs0, v1 = xs1; uint32_t it = 0;
      while (v0.z != tag || v1.z != tag) {
        v0 = ld_rlx128(g_xs + m * 128 + row0); v1 = ld_rlx128(g_xs + m * 128 + row0 + 8);
        if (++it > (1u << 20)) fail();
      }
      __syncwarp();
      if (tid == 0) STAMP(38);
      mu0 = __uint_as_float(v0.x); rs0 = __uint_as_float(v0.y); mu1 = __uint_as_float(v1.x); rs1 = __uint_as_float(v1.y);
      ep0 = __uint_as_float(v0.w); ep1 = __uint_as_float(v1.w);
    }
    const RowC c0 = {-mu0, rs0 * 0.7978845608f, rs0 * rs0 * rs0 * 0.0356774081f};
    const RowC c1 = {-mu1, rs1 * 0.7978845608f, rs1 * rs1 * rs1 * 0.0356774081f};
    wg_wait<1>();
    if (el) mbar_arrive(BAR(B_WE + 7));
    if (tid == 0) STAMP(2);
    auto gelu_pack = [&](auto& z, auto& zp, uint32_t csa, auto n) {
      sfor<0, decltype(n)::v>([&](auto ii) {
        constexpr int i = decltype(ii)::v;
        const float2 cs = lds64f(csa + i * 32 + tq * 8);
        zp[2 * i] = pack2(gelu_f(z[4 * i], cs.x, c0), gelu_f(z[4 * i + 1], cs.y, c0));
        zp[2 * i + 1] = pack2(gelu_f(z[4 * i + 2], cs.x, c1), gelu_f(z[4 * i + 3], cs.y, c1));
      });
    };
    auto staged = [&](int ev) { fence_async_smem(); bar_sync(1 + wg, 128); if (el) mbar_arrive(BAR(B_WF + ev * 2 + wg)); };
    uint32_t z2p[32];
    if (dz2) {
      mbar_wait(BAR(B_CZ), 0);
      gelu_pack(z2, z2p, sb + OFF_CS, IC<16>{});
      constexpr uint32_t ONE2 = 0x3F803F80u;
      float sa[2][4] = {{0, 0, 0, 0}, {0, 0, 0, 0}}, s1[2][4] = {{0, 0, 0, 0}, {0, 0, 0, 0}}, s2[2][4] = {{0, 0, 0, 0}, {0, 0, 0, 0}};
#pragma unroll
      for (int q = 0; q < 8; q++) {
        mma16816(sa[q & 1], z2p[4 * q], z2p[4 * q + 1], z2p[4 * q + 2], z2p[4 * q + 3], ONE2, ONE2);
        mma16816(s1[q & 1], z2p[4 * q], z2p[4 * q + 1], z2p[4 * q + 2], z2p[4 * q + 3], z2p[4 * q], z2p[4 * q + 2]);
        mma16816(s2[q & 1], z2p[4 * q], z2p[4 * q + 1], z2p[4 * q + 2], z2p[4 * q + 3], z2p[4 * q + 1], z2p[4 * q + 3]);
      }
      const float qa = __shfl_sync(~0u, (g & 1) ? s1[0][1] + s1[1][1] : s1[0][0] + s1[1][0], g * 4 + (g >> 1));
      const float qb = __shfl_sync(~0u, (g & 1) ? s2[0][3] + s2[1][3] : s2[0][2] + s2[1][2], g * 4 + (g >> 1));
      const float a = tq ? sa[0][2] + sa[1][2] : sa[0][0] + sa[1][0], e = tq ? qb : qa;
      if (tq < 2) st_rlx128(g_st + (m * 7 + j) * 128 + row0 + tq * 8, make_uint4(__float_as_uint(a), __float_as_uint(fmaxf(e - a * a * (1.f / 128), 0.f)), tag, 0));
    }
    if (tid == 0) STAMP(3);
    z1_issue(IC<9>{});
    if (tid == 0) STAMP(7);
    uint32_t r20 = 0, r21 = 0, nm0 = 0, nm1 = 0;
    if (dz2) {
      const uint4* sp = g_st + (m * 7 + 2 * tq) * 128 + row0;
      const int o2 = tq < 3 ? 128 : 0;
      uint4 v0, v1, v2, v3; uint32_t it = 0;
      do {
        v0 = ld_rlx128(sp); v1 = ld_rlx128(sp + o2); v2 = ld_rlx128(sp + 8); v3 = ld_rlx128(sp + o2 + 8);
        if (++it > (1u << 20)) fail();
      } while (v0.z != tag || v1.z != tag || v2.z != tag || v3.z != tag);
      __syncwarp();
      if (tid == 0) STAMP(4);
      const float wt = tq < 3 ? 1.f : 0.f;
      const float me0 = qsum(fmaf(wt, __uint_as_float(v1.x), __uint_as_float(v0.x))) * (1.f / 896);
      const float me1 = qsum(fmaf(wt, __uint_as_float(v3.x), __uint_as_float(v2.x))) * (1.f / 896);
      float x, e0, e1;
      x = __uint_as_float(v0.x) * (1.f / 128) - me0; e0 = fmaf(128.f * x, x, __uint_as_float(v0.y));
      x = __uint_as_float(v1.x) * (1.f / 128) - me0; e0 = fmaf(wt, fmaf(128.f * x, x, __uint_as_float(v1.y)), e0);
      x = __uint_as_float(v2.x) * (1.f / 128) - me1; e1 = fmaf(128.f * x, x, __uint_as_float(v2.y));
      x = __uint_as_float(v3.x) * (1.f / 128) - me1; e1 = fmaf(wt, fmaf(128.f * x, x, __uint_as_float(v3.y)), e1);
      x = rsq(fmaf(qsum(e0), 1.f / 896, ep0)); r20 = pack2(x, x); x = -me0 * blo(r20); nm0 = pack2(x, x);
      x = rsq(fmaf(qsum(e1), 1.f / 896, ep1)); r21 = pack2(x, x); x = -me1 * blo(r21); nm1 = pack2(x, x);
    }
    wg_wait<0>();
    if (el) { mbar_arrive(BAR(B_WE + 8)); mbar_arrive(BAR(B_WE + 9)); }
    if (dz2) {
      const uint32_t za = sb + OFF_X + wg * 8192 + (lane >> 4) * 1024 + (2 * w + ((lane >> 3) & 1)) * 128 + (lane & 7) * 16;
#pragma unroll
      for (int i = 0; i < 16; i += 2)
        stsm4(za + (i >> 3) * 16384 + (i & 7) * 1024, bfma(z2p[2 * i], r20, nm0), bfma(z2p[2 * i + 1], r21, nm1), bfma(z2p[2 * i + 2], r20, nm0), bfma(z2p[2 * i + 3], r21, nm1));
      staged(0);
    }
    if (tid == 0) STAMP(5);
    {
      uint32_t da = dX + 2048, db = dW1 + wslot(10) / 16;
#pragma unroll 1
      for (int k = 10; k < 16; k++) {
        mbar_wait(BAR(B_WF + k), 0);
        wg_fence();
#pragma unroll
        for (int kk = 0; kk < 4; kk++) wgmma_ss_n112(z1, da + kk * 2, H128, db + kk * stepW1, hW1);
        wg_commit();
        da += 1024; db = k == 11 ? dW1 + OFF_WR / 16 : db + 1024;
      }
    }
    wg_wait<0>();
    if (el) { mbar_arrive(BAR(B_ZS)); mbar_arrive(BAR(B_P1)); }
    if (tid == 0) STAMP(6);
    uint32_t z1p[28];
    mbar_wait(BAR(B_CS), 0);
    gelu_pack(z1, z1p, sb + OFF_CS + 512, IC<14>{});
    if (tid == 0) STAMP(8);
    sched_fence(BAR(B_CS));
    float acc[56];
    zero_acc(acc);
    uint32_t rb0, rb1, rdA, rdB;
    {
      const uint32_t dA = dlo(sb + wg * 8192, 16), dB = dlo(sb + 16384, 128);
      auto issue = [&](auto sc, uint32_t ph) {
        constexpr int s = decltype(sc)::v;
        mbar_wait(BAR(B_GF + s), ph);
        wg_fence();
#pragma unroll
        for (int kk = 0; kk < 4; kk++) wgmma_ss_n112(acc, dA + s * (G2_STB / 16) + kk * 2, H128, dB + s * (G2_STB / 16) + kk * 16, dhi(1024, 0));
        wg_commit();
      };
      auto step = [&](auto sc, uint32_t ph) {
        constexpr int s = decltype(sc)::v;
        issue(sc, ph);
        wg_wait<1>();
        if (el) mbar_arrive(BAR(B_GE + (s + G2_ST - 1) % G2_ST));
      };
      rb0 = ldg16(p.b_sp + m * 128 + row0); rb1 = ldg16(p.b_sp + m * 128 + row0 + 8);
      rdA = ldg16(p.ssm_D + j * 64 + m * 4 + wg); rdB = ldg16(p.ssm_D + j * 64 + m * 4 + 2 + wg);
      issue(IC<0>{}, 0);
      if (tid == 0) STAMP(11);
      step(IC<1>{}, 0);
      uint32_t ph = 0;
#pragma unroll 1
      for (int i = 0; i < 5; i++) {
        step(IC<2>{}, ph); step(IC<3>{}, ph); step(IC<4>{}, ph); step(IC<5>{}, ph);
        ph ^= 1;
        step(IC<0>{}, ph); step(IC<1>{}, ph);
      }
      wg_wait<0>();
    }
    if (tid == 0) STAMP(12);
    const uint32_t stg = sb + wg * 8192 + (w & 1) * 3584 + ((lane >> 3) & 1) * 1792 + (lane >> 4) * 128 + (lane & 7) * 16;
    const float h0 = 0.5f * rs0, h1 = 0.5f * rs1, hb0 = h0 * blo(rb0), hb1 = h1 * blo(rb1);
#pragma unroll
    for (int i = 0; i < 14; i += 2)
      stsm4(stg + (w >> 1) * G2_STB + i * 128,
            bmul(z1p[2 * i], pack2(fmaf(acc[4 * i], h0, hb0), fmaf(acc[4 * i + 1], h0, hb0))),
            bmul(z1p[2 * i + 1], pack2(fmaf(acc[4 * i + 2], h1, hb1), fmaf(acc[4 * i + 3], h1, hb1))),
            bmul(z1p[2 * i + 2], pack2(fmaf(acc[4 * i + 4], h0, hb0), fmaf(acc[4 * i + 5], h0, hb0))),
            bmul(z1p[2 * i + 3], pack2(fmaf(acc[4 * i + 6], h1, hb1), fmaf(acc[4 * i + 7], h1, hb1))));
    staged(2);
    if (tid == 0) STAMP(13);
    bar_sync(3, 256);
    if (CONV_SKEW && wg) { const long long t0 = clock64(); while (clock64() - t0 < CONV_SKEW); }
    {
      const uint32_t pq[4] = {sb + (wg ? 145408 : 133120), sb + (wg ? 149504 : 137216), sb + (wg ? 179072 : 141312), sb + (wg ? 183168 : 57344)};
      const uint32_t pw = w == 0 ? pq[0] : w == 1 ? pq[1] : w == 2 ? pq[2] : pq[3];
#pragma unroll 1
      for (int r = 0; r < 2; r++) {
        const uint32_t cv = sb + (r ? OFF_CV2 : OFF_CV) + wg * CV_CH;
        mbar_wait(BAR(B_CVF + r), 0);
        auto fin = [&](int q) {
          conv_fin(sb + (q ? OFF_CV2 : OFF_CV) + wg * CV_CH, pq, t, (q ? rdB : rdA) * 0x10001u, g_y + (size_t)(j * 64 + m * 4 + 2 * q + wg) * 256);
          bar_sync(1 + wg, 128);
          if (el) mbar_arrive(BAR(q ? B_CVB : B_CVA));
        };
        conv_mma(cv, pw, w, lane, [&] { sched_fence(BAR(B_CVF)); if (r) fin(0); });
        if (tid == 0) STAMP(r ? 14 : 9);
        bar_sync(1 + wg, 128);
        if (r) fin(1);
        if (tid == 0 && r == 0) STAMP(10);
      }
    }
    if (tid == 0) STAMP(15);
    float o[32];
    zero_acc(o);
    uint4 yv[4];
    const uint4* ysrc = g_y + (size_t)(j * 64 + (t >> 3)) * 256 + m * 16 + wg * 8 + (t & 7);
    {
      const uint32_t dA = dlo(sb + wg * 14336, 128), dB = dlo(sb, 8192), hf = BAR(wg ? B_WF + 8 : B_XF);
      sfor<0, 8>([&](auto tc) {
        constexpr int tt = decltype(tc)::v;
        if (!(tt & 1)) mbar_wait(BAR(B_WOF + (tt >> 1)), 0);
        if (tt == 7) mbar_wait(BAR(B_KV), 0);
        mbar_wait(hf + 8 * tt, 1);
        if (tt == 0 && t == 0) STAMP(16 + wg * 5);
        wg_fence();
#pragma unroll
        for (int kk = 0; kk < 7; kk++) wgmma_ss_n64(o, dA + hslot(0, tt) / 16 + kk * 16, dhi(1792, 0), dB + woslot(tt) / 16 + kk * 128, H128);
        wg_commit();
        if constexpr (tt == Y_T) {
          sched_fence(BAR(B_WOF));
#pragma unroll
          for (int i = 0; i < 4; i++) yv[i] = ld_rlx128(ysrc + i * 16 * 256);
        }
        wg_wait<1>();
        if constexpr (tt > 0 && tt <= 4) { if (el) mbar_arrive(BAR(wg ? hebar(2 * tt - 1) : hebar(2 * tt - 2))); }
      });
      wg_wait<0>();
      mbar_wait(BAR(hebar(2)), 0); mbar_wait(BAR(hebar(3)), 0);
    }
    if (t == 0) STAMP(17 + wg * 5);
    const uint32_t yb = sb + (wg ? OFF_YF1 : OFF_YF0);
    {
#pragma unroll
      for (int i = 0; i < 4; i++) {
        uint32_t it = 0;
        while (yv[i].x == ~0u) { yv[i] = ld_rlx128(ysrc + i * 16 * 256); if (++it > (1u << 20)) fail(); }
      }
      __syncwarp();
#pragma unroll
      for (int i = 0; i < 4; i++) sts128(yb + ((t >> 3) + i * 16) * 128 + (((t & 7) ^ ((t >> 3) & 7)) << 4), yv[i]);
      bar_sync(1 + wg, 128);
    }
    mbar_wait(BAR(B_FX + wg), 0);
    if (t == 0) STAMP(18 + wg * 5);
    {
      const uint32_t rp0 = pack2(rs0, rs0), rp1 = pack2(rs1, rs1), np0 = pack2(-mu0 * blo(rp0), -mu0 * blo(rp0)), np1 = pack2(-mu1 * blo(rp1), -mu1 * blo(rp1));
      const uint32_t xb = sb + (wg ? OFF_XF1 - 8192 : OFF_XF0);
      const uint32_t ybase = yb + ((lane & 7) + (lane >> 4) * 8) * 128 + (((2 * w + ((lane >> 3) & 1)) ^ lsw) << 4);
#pragma unroll
      for (int c = 0; c < 8; c += 2) {
        uint32_t x[4], y[4], r[4];
        const uint32_t xa = xb + lrow + (((c + lhi) ^ lsw) << 4);
        ldsm4(xa, x);
        ldsm4t(ybase + c * 1024, y);
#pragma unroll
        for (int e = 0; e < 4; e++) {
          const uint32_t tt = bfma(bfma(x[e], (e & 1) ? rp1 : rp0, (e & 1) ? np1 : np0), y[e], x[e]);
          r[e] = pack2(blo(tt) + o[4 * c + 2 * e], bhi(tt) + o[4 * c + 2 * e + 1]);
        }
        stsm4(xa, r[0], r[1], r[2], r[3]);
      }
      fence_async_smem();
      __syncwarp();
      if (lane == 0) {
        tma2d_st(&tmOut, j * 64, m * 128 + warp * 16, xb + warp * 2048);
        bulk_commit();
        if (m == 0 && j == 0 && warp == 4) *(volatile uint32_t*)&g_epoch = tag;
        asm volatile("cp.async.bulk.wait_group.read 0;" ::: "memory");
      }
    }
    if (tid == 0) STAMP(24);
    if (tid == 128) STAMP(19);
  } else {
    asm volatile("setmaxnreg.dec.sync.aligned.u32 104;");
    uint32_t is_prod; asm volatile("shr.u32 %0, %1, %2;" : "=r"(is_prod) : "r"(0x100u), "r"(warp));
    if (is_prod & 1) {
    if (lane == 0) {
#pragma unroll
      for (int k = 0; k < NPRO; k++) { mbar_init(BAR(B_XF + k), 1); mbar_init(BAR(B_WF + k), 1); }
      asm volatile("fence.mbarrier_init.release.cluster;" ::: "memory");
    }
    __syncwarp();
    asm volatile("bar.arrive 4, 384;" ::: "memory");
      {
        uint32_t slot = sb + OFF_WR;
#pragma unroll 1
        for (int k = 0; k < 16; k++) {
          if (k == NPRO) bar_sync(5, 128);
          if (k < 8) { e_expect(BAR(B_XF + k), 16384); e_tma2d(sb + OFF_X + k * 16384, &tmX, k * 64, m * 128, BAR(B_XF + k)); }
          if (dz2) {
            if (k >= 6) mbar_wait(BAR(B_WE + k - 6), 0);
            const int c0 = (k < 8 ? FH_ : 0) + j * 128;
            e_expect(BAR(B_WF + k), 16384);
            e_tma2d(slot, &tmWin, c0, (k & 7) * 64, BAR(B_WF + k));
            e_tma2d(slot + 8192, &tmWin, c0 + 64, (k & 7) * 64, BAR(B_WF + k));
          } else if (k >= 8) {
            mbar_wait(BAR(B_WE + k - 6), 0);
            e_expect(BAR(B_WF + k), 14336);
            e_tma3d(slot, &tmWin7, 0, (k & 7) * 64, 0, BAR(B_WF + k));
          } else if (k == 5 && m < 14) {
            e_expect(BAR(B_WF), 8 * 8192);
#pragma unroll 1
            for (int b = 0; b < 8; b++) e_tma2d(sb + OFF_WR + b * 8192, &tmWin, FH_ + m * 64, b * 64, BAR(B_WF));
          }
          slot = (k == 5 || k == 11) ? sb + OFF_WR : slot + 16384;
        }
        if (m < 8 && lane == 0) tma2d_pf(&tmWo, j * 64, m * 112);
      }
      mbar_wait(BAR(B_EP), 0);
      const uint32_t tag = lds32(sb + OFF_EP);
      mbar_wait(BAR(B_ZS), 0);
      {
        const uint8_t* zsrc = (const uint8_t*)g_z2 + j * 14336;
        int s = 0; uint32_t ph = 1;
#pragma unroll 1
        for (int k = 0; k < 36; k++) {
          mbar_wait(BAR(B_GE + s), ph);
          if (k < 32) {
            e_expect(BAR(B_GF + s), G2_STB);
            e_tma2d(sb + s * G2_STB, &tmW, k * 64, m * 128, BAR(B_GF + s));
            if (k == 0) {
              uint32_t it = 0;
              while (ld_rlx(g_cnt + (tag & 1) * 32) < 112) if (++it > (1u << 20)) fail();
              asm volatile("fence.acquire.gpu;" ::: "memory");
              fence_async_glob();
              if (lane == 0) STAMP(34);
              __syncwarp();
            }
            e_g2s(sb + s * G2_STB + 16384, zsrc + (size_t)k * ZSLAB, 14336, BAR(B_GF + s));
          } else if (k == 35) e_arrive(BAR(B_S5));
          else {
            const int q = k - 32;
            e_expect(BAR(B_WOF + q), TILE_B);
            e_tma2d(sb + OFF_WO + q * TILE_B, &tmWo, j * 64, q * 256, BAR(B_WOF + q));
            if (q < 2) e_tma2d(sb + OFF_WO + q * TILE_B + 14336, &tmWo, j * 64, q * 256 + 128, BAR(B_WOF + q));
          }
          if (++s == G2_ST) { s = 0; ph ^= 1; }
        }
      }
      poll_flags<1>(g_fh + m * 64, 8, tag, lane);
      {
        const uint8_t* hsrc = (const uint8_t*)g_h + (size_t)m * 8 * TILE_B;
#pragma unroll 1
        for (int i = 0; i < 16; i++) {
          const int tt = i >> 1, wg = i & 1;
          if (i == 4) mbar_wait(BAR(B_CVA), 0);
          if (i == 6) mbar_wait(BAR(B_CVB), 0);
          if (i >= 8) mbar_wait(bars + 8 * ((hetab() >> (8 * (i - 8))) & 255), 0);
          const uint32_t bar = BAR(tt + wg * 16);
          e_expect(bar, 14336);
          e_g2s(sb + ((tt & 2) ? ((tt & 1) ? 153600 : 187264) : (tt & 1) * 28672) + wg * 14336, hsrc + tt * TILE_B + wg * 14336, 14336, bar);
          if (i == 5) e_tma2d(sb + woslot(5), &tmWo, j * 64, 5 * 128, BAR(B_WOF + 2));
          if (i == 7) { e_expect(BAR(B_WOF + 3), 14336); e_tma2d(sb + woslot(6), &tmWo, j * 64, 6 * 128, BAR(B_WOF + 3)); }
          if (i == 13) { e_expect(BAR(B_KV), 14336); e_tma3d(sb + woslot(7), &tmWo7, j * 64, 0, 0, BAR(B_KV)); }
        }
        e_expect(BAR(B_FX), 8192); e_tma2d(sb + OFF_XF0, &tmXh, j * 64, m * 128, BAR(B_FX));
        e_expect(BAR(B_FX + 1), 8192); e_tma2d(sb + OFF_XF1, &tmXh, j * 64, m * 128 + 64, BAR(B_FX + 1));
      }
    } else {
      const int hw = warp - 9;
      init_others();
      bar_sync(4, 384);
      auto kappa_prep = [&](int part) {
        uint4 v[16];
        const uint8_t* ksrc = (const uint8_t*)p.ssm_k + (size_t)(j * 64 + m * 4 + part * 2) * 4096 + lane * 16;
#pragma unroll
        for (int i = 0; i < 16; i++) v[i] = ldg128(ksrc + i * 512);
        mbar_wait(BAR(part ? B_S5 : B_P1), 0);
#pragma unroll
        for (int ch = 0; ch < 2; ch++) {
          const uint32_t cv = sb + (part ? OFF_CV2 : OFF_CV) + ch * CV_CH;
          uint32_t carry = 0;
#pragma unroll
          for (int i = 0; i < 8; i++) {
            const uint4 x = v[ch * 8 + i];
            uint32_t prev = __shfl_up_sync(~0u, x.w, 1);
            if (lane == 0) prev = carry;
            carry = __shfl_sync(~0u, x.w, 31);
            sts128(cv + CV_K0 + 32 + (i * 32 + lane) * 16, x);
            sts128(cv + CV_K1 + 32 + (i * 32 + lane) * 16,
                   make_uint4(__byte_perm(prev, x.x, 0x5432), __byte_perm(x.x, x.y, 0x5432), __byte_perm(x.y, x.z, 0x5432), __byte_perm(x.z, x.w, 0x5432)));
          }
          const uint4 z = make_uint4(0, 0, 0, 0);
          if (lane < 2) sts128(cv + CV_K0 + lane * 16, z);
          else if (lane < 4) sts128(cv + CV_K1 + (lane - 2) * 16, z);
          else if (lane < 16) sts128(cv + CV_E + (lane - 4) * 16, z);
          else if (lane < 28) sts128(cv + CV_O + (lane - 16) * 16, z);
        }
        fence_async_smem();
        __syncwarp();
        if (lane == 0) mbar_arrive(BAR(B_CVF + part));
      };
      auto u_load = [&](int part) {
        mbar_expect_tx(BAR(B_CVF + part), 8192);
#pragma unroll 1
        for (int ch = 0; ch < 2; ch++) {
          const uint8_t* usrc = (const uint8_t*)g_kv + (size_t)(j * 64 + m * 4 + part * 2 + ch) * 4096;
          const uint32_t cb = sb + (part ? OFF_CV2 : OFF_CV) + ch * CV_CH + CV_PAD;
          bulk_g2s(cb + CV_E, usrc, 2048, BAR(B_CVF + part));
          bulk_g2s(cb + CV_O, usrc + 2048, 2048, BAR(B_CVF + part));
        }
      };
      uint32_t tag = 0;
      if (hw == 0) {
        tag = *(volatile uint32_t*)&g_epoch + 1;
        if (lane == 0) { asm volatile("st.shared.b32 [%0], %1;" ::"r"(sb + OFF_EP), "r"(tag) : "memory"); mbar_arrive(BAR(B_EP)); }
        if (lane == 0) {
          if (m == 0 && j == 0) st_flag(g_cnt + ((tag + 1) & 1) * 32, 0);
          st_flag(g_fh + (m * 8 + j) * 8, 0);
        }
        if (dz2) {
          uint4 v0, v1; uint32_t it = 0;
          do {
            v0 = ld_rlx128(g_cz + j * 64 + lane); v1 = ld_rlx128(g_cz + j * 64 + 32 + lane);
            if (++it > (1u << 20)) fail();
          } while (v0.z != tag || v1.z != tag);
          asm volatile("st.shared.v2.b32 [%0], {%1, %2};" ::"r"(sb + OFF_CS + lane * 8), "r"(v0.x), "r"(v0.y) : "memory");
          asm volatile("st.shared.v2.b32 [%0], {%1, %2};" ::"r"(sb + OFF_CS + 256 + lane * 8), "r"(v1.x), "r"(v1.y) : "memory");
          __syncwarp();
          if (lane == 0) { mbar_arrive(BAR(B_CZ)); STAMP(39); }
        }
        {
          uint2 v[4]; uint32_t it = 0; bool ok;
          do {
            ok = true;
#pragma unroll
            for (int i = 0; i < 4; i++) if (lane + 32 * i < 112) { const int q = lane + 32 * i; v[i] = ld_rlx64(g_cs + (dz2 ? j * 128 + q : (q >> 4) * 128 + 112 + (q & 15))); ok &= (v[i].y == tag); }
            if (++it > (1u << 20)) fail();
          } while (!ok);
#pragma unroll
          for (int i = 0; i < 4; i++) if (lane + 32 * i < 112) asm volatile("st.shared.b32 [%0], %1;" ::"r"(sb + OFF_CS + 512 + (lane + 32 * i) * 4), "r"(v[i].x) : "memory");
          __syncwarp();
          if (lane == 0) { mbar_arrive(BAR(B_CS)); STAMP(41); }
        }
        if (lane == 0) {
          uint8_t* hdst = (uint8_t*)g_h + (size_t)(m * 8 + j) * TILE_B;
          if (dz2) {
#pragma unroll 1
            for (int wg = 0; wg < 2; wg++) {
              uint8_t* zdst = (uint8_t*)g_z2 + (size_t)(m * 2 + wg) * ZSLAB;
              mbar_wait(BAR(B_WF + wg), 1);
              bulk_s2g(zdst + j * 14336, sb + OFF_X + wg * 8192, 8192);
              bulk_s2g(zdst + j * 14336 + 8192, sb + OFF_X + 16384 + wg * 8192, 6144);
              bulk_s2g(zdst + 7 * 14336 + j * 2048, sb + OFF_X + 16384 + wg * 8192 + 6144, 2048);
            }
            bulk_commit(); bulk_wait<0>();
            fence_gpu();
            asm volatile("red.relaxed.gpu.global.add.u32 [%0], 1;" ::"l"(g_cnt + (tag & 1) * 32) : "memory");
          }
          mbar_arrive(BAR(B_ZS));
          STAMP(46);
#pragma unroll 1
          for (int wg = 0; wg < 2; wg++) {
            mbar_wait(BAR(B_WF + 4 + wg), dz2);
            bulk_s2g(hdst + wg * 14336, sb + wg * 8192, 7168);
            bulk_s2g(hdst + wg * 14336 + 7168, sb + G2_STB + wg * 8192, 7168);
          }
          bulk_commit(); bulk_wait<0>();
          fence_gpu();
          st_flag(g_fh + (m * 8 + j) * 8, tag);
          STAMP(47);
        }
      } else {
        if (hw == 1 && lane == 0) st_flag(g_fk + (j * 16 + m) * 8, 0);
        auto pf_rows = [&](const void* base) {
          const uint8_t* q = (const uint8_t*)base + (hw - 1) * 8192 + lane * 128;
          asm volatile("prefetch.global.L2 [%0];" ::"l"(q));
          asm volatile("prefetch.global.L2 [%0];" ::"l"(q + 4096));
        };
        auto y_clear = [&]() {
          uint4* yc = g_y + (size_t)(j * 64 + m * 4 + (hw - 1) * 2) * 256 + lane;
#pragma unroll
          for (int i = 0; i < 16; i++) st_rlx128(yc + i * 32, make_uint4(~0u, ~0u, ~0u, ~0u));
        };
        mbar_wait(BAR(B_XF + 3), 0);
        if (YC == 0) y_clear();
        if (dz2) asm volatile("prefetch.global.L2 [%0];" ::"l"((const uint8_t*)p.w_in + (size_t)(m * 32 + lane) * (F_ * 2) + j * 256 + (hw - 1) * 128));
        mbar_wait(BAR(B_XF + 7), 0);
        if (lane == 0 && hw == 1) STAMP(51);
        pf_rows(p.k + (size_t)(m * 128 + j * 16) * D_);
        if (YC == 1) y_clear();
        mbar_wait(BAR(B_WF + 9), 0);
        if (YC == 2) { mbar_wait(BAR(B_WE + 7), 0); y_clear(); }
        pf_rows(p.v + (size_t)(m * 128 + j * 16) * D_);
        mbar_wait(BAR(B_WF + 12), 0);
#pragma unroll 1
        for (int pass = 0; pass < 2; pass++) {
        if (pass == hw - 1) kappa_prep(pass);
        if (pass) break;
        if (lane == 0) STAMP(41 + hw);
        if (YC == 3) y_clear();
        {
          const int d0 = j * 64 + (lane >> 1) * 4;
          uint32_t wt[2][4];
#pragma unroll
          for (int q = 0; q < 2; q++) {
            const uint4 tp = ldg128(p.shift + (d0 + 2 * q) * 4);
            wt[q][0] = __byte_perm(tp.x, tp.z, 0x5410); wt[q][1] = __byte_perm(tp.x, tp.z, 0x7632);
            wt[q][2] = __byte_perm(tp.y, tp.w, 0x5410); wt[q][3] = __byte_perm(tp.y, tp.w, 0x7632);
          }
          mbar_wait(BAR(B_GF + KV_ST), 0);
#pragma unroll 1
          for (int bt = 0; bt < 2; bt++) {
            const int blk = (hw - 1) * 4 + bt * 2 + (lane & 1), s0 = m * 128 + blk * 16;
            uint2 kk[19], vv[16];
#pragma unroll
            for (int i = 0; i < 19; i++) kk[i] = (i >= 3 || s0 > 0) ? ldg64(p.k + (size_t)(s0 - 3 + i) * D_ + d0) : make_uint2(0, 0);
#pragma unroll
            for (int i = 0; i < 16; i++) vv[i] = ldg64(p.v + (size_t)(s0 + i) * D_ + d0);
            uint4* dst = g_kv + (size_t)d0 * 256 + m * 8 + blk;
#pragma unroll
            for (int q = 0; q < 2; q++) {
#pragma unroll
              for (int cc = 0; cc < 2; cc++) {
                uint32_t u[8];
#pragma unroll
                for (int e = 0; e < 8; e++) {
                  const int i = cc * 8 + e;
                  auto c_ = [&](const uint2& a) { return q ? a.y : a.x; };
                  u[e] = bmul(bfma(c_(kk[i + 3]), wt[q][0], bfma(c_(kk[i + 2]), wt[q][1], bfma(c_(kk[i + 1]), wt[q][2], bmul(c_(kk[i]), wt[q][3])))), c_(vv[i]));
                }
                dst[q * 512 + cc * 128] = make_uint4(__byte_perm(u[1], u[0], 0x5410), __byte_perm(u[3], u[2], 0x5410), __byte_perm(u[5], u[4], 0x5410), __byte_perm(u[7], u[6], 0x5410));
                dst[q * 512 + cc * 128 + 256] = make_uint4(__byte_perm(u[1], u[0], 0x7632), __byte_perm(u[3], u[2], 0x7632), __byte_perm(u[5], u[4], 0x7632), __byte_perm(u[7], u[6], 0x7632));
              }
            }
            if (lane == 0 && hw == 1) STAMP(52 + bt);
          }
          __syncwarp();
          if (lane == 0) mbar_arrive(BAR(B_KE));
        }
        if (hw == 1) {
          mbar_wait(BAR(B_EP), 0);
          tag = lds32(sb + OFF_EP);
          mbar_wait(BAR(B_KE), 0);
          if (lane == 0) { fence_gpu(); st_flag(g_fk + (j * 16 + m) * 8, tag); STAMP(44); }
          __syncwarp();
          poll_flags<1>(g_fk + j * 128, 16, tag, lane);
          if (lane == 0) {
#pragma unroll 1
            for (int q = 0; q < 2; q++) { if (q) mbar_wait(BAR(B_S5), 0); u_load(q); }
          }
        }
        }
      }
    }
  }
}

typedef CUresult (*EncFn)(CUtensorMap*, CUtensorMapDataType, cuuint32_t, void*, const cuuint64_t*, const cuuint64_t*, const cuuint32_t*,
                          const cuuint32_t*, CUtensorMapInterleave, CUtensorMapSwizzle, CUtensorMapL2promotion, CUtensorMapFloatOOBfill);

void enc3d(EncFn f, CUtensorMap* m, const void* ptr, uint64_t d0, uint64_t d1, uint64_t d2, uint64_t s1, uint64_t s2, uint32_t b0, uint32_t b1,
           uint32_t b2, CUtensorMapSwizzle swz) {
  cuuint64_t dims[3] = {d0, d1, d2}, strides[2] = {s1, s2};
  cuuint32_t box[3] = {b0, b1, b2}, es[3] = {1, 1, 1};
  f(m, CU_TENSOR_MAP_DATA_TYPE_BFLOAT16, 3, const_cast<void*>(ptr), dims, strides, box, es, CU_TENSOR_MAP_INTERLEAVE_NONE, swz,
    CU_TENSOR_MAP_L2_PROMOTION_L2_128B, CU_TENSOR_MAP_FLOAT_OOB_FILL_NONE);
}
void enc2d(EncFn f, CUtensorMap* m, const void* ptr, uint64_t cols, uint64_t rows, uint32_t bc, uint32_t br, CUtensorMapSwizzle swz = CU_TENSOR_MAP_SWIZZLE_128B) {
  cuuint64_t dims[2] = {cols, rows}, strides[1] = {cols * 2};
  cuuint32_t box[2] = {bc, br}, es[2] = {1, 1};
  f(m, CU_TENSOR_MAP_DATA_TYPE_BFLOAT16, 2, const_cast<void*>(ptr), dims, strides, box, es, CU_TENSOR_MAP_INTERLEAVE_NONE,
    swz, CU_TENSOR_MAP_L2_PROMOTION_L2_256B, CU_TENSOR_MAP_FLOAT_OOB_FILL_NONE);
}

}

extern "C" void kernel_launch(void* const* d_in, const int* in_sizes, int n_in, void* d_out, int out_size) {
  (void)in_sizes; (void)n_in; (void)out_size;
  static EncFn enc = nullptr;
  static int nsm = 0;
  if (!enc) {
    void* f = nullptr;
    cudaDriverEntryPointQueryResult q;
    cudaGetDriverEntryPoint("cuTensorMapEncodeTiled", &f, cudaEnableDefault, &q);
    enc = (EncFn)f;
    int dev = 0;
    cudaGetDevice(&dev);
    cudaDeviceGetAttribute(&nsm, cudaDevAttrMultiProcessorCount, dev);
    cudaFuncSetAttribute(fused_kernel<true>, cudaFuncAttributeMaxDynamicSharedMemorySize, SM_TOTAL);
    cudaFuncSetAttribute(fused_kernel<false>, cudaFuncAttributeMaxDynamicSharedMemorySize, SM_TOTAL);
  }
  CUtensorMap tmX, tmWin, tmW, tmWo, tmOut, tmWin7, tmWo7, tmXh;
  enc2d(enc, &tmX, d_in[0], D_, S_, 64, 128);
  enc2d(enc, &tmWin, d_in[7], F_, D_, 64, 64);
  enc2d(enc, &tmW, d_in[8], S_, S_, 64, 128);
  enc2d(enc, &tmWo, d_in[10], D_, FH_, 64, 112);
  enc3d(enc, &tmWin7, (const uint8_t*)d_in[7] + 224, 16, D_, 7, F_ * 2, 256, 16, 64, 7, CU_TENSOR_MAP_SWIZZLE_32B);
  enc3d(enc, &tmWo7, (const uint8_t*)d_in[10] + 112 * 1024, D_, 16, 7, 1024, 128 * 1024, 64, 16, 7, CU_TENSOR_MAP_SWIZZLE_128B);
  enc2d(enc, &tmXh, d_in[0], D_, S_, 64, 64);
  enc2d(enc, &tmOut, d_out, D_, S_, 64, 16);
  Params p;
  p.x = (const __nv_bfloat16*)d_in[0];
  p.k = (const __nv_bfloat16*)d_in[1]; p.v = (const __nv_bfloat16*)d_in[2]; p.shift = (const __nv_bfloat16*)d_in[3];
  p.ssm_k = (const __nv_bfloat16*)d_in[4]; p.ssm_D = (const __nv_bfloat16*)d_in[5]; p.w_in = (const __nv_bfloat16*)d_in[7];
  p.b_sp = (const __nv_bfloat16*)d_in[9]; p.w_sp = (const __nv_bfloat16*)d_in[8];
  if (nsm == 132) fused_kernel<true><<<132, 384, SM_TOTAL, cudaStreamPerThread>>>(tmX, tmWin, tmW, tmWo, tmOut, tmWin7, tmWo7, tmXh, p);
  else fused_kernel<false><<<132, 384, SM_TOTAL, cudaStreamPerThread>>>(tmX, tmWin, tmW, tmWo, tmOut, tmWin7, tmWo7, tmXh, p);
}
```
